```python
import torch

def _softmax(x, axis=-1):
    return torch.softmax(x, dim=axis)

def _gelu(x):
    return torch.nn.functional.gelu(x, approximate='tanh')

def _silu(x):
    return torch.nn.functional.silu(x)

def _sigmoid(x):
    return torch.sigmoid(x)

def _layernorm(x, axis=-1, eps=1e-05):
    m = x.mean(dim=axis, keepdim=True)
    v = x.var(dim=axis, keepdim=True, unbiased=False)
    return (x - m) / torch.sqrt(v + eps)

def _scatter_add(tgt, idx, src, axis=0):
    return tgt.clone().index_add_(axis, idx, src)

def _segment_sum(src, seg, n):
    out = torch.zeros((n,) + src.shape[1:], dtype=src.dtype)
    return out.index_add_(0, seg, src)

def _pad(x, pw):
    flat = tuple((v for pair in reversed(pw) for v in pair))
    return torch.nn.functional.pad(x, flat)
kernel_name = 'adaLN_cond__ssm_conv_s4d__geglu_ffn__prompt'

def setup_inputs():

    _w = lambda a: (lambda t: t.to(torch.bfloat16) if t.is_floating_point() else t)(torch.as_tensor(a))

    def _A_setup():
        Bsz, L, D, N = (1, 2048, 640, 128)
        return {'u': _w((lambda *s: torch.randn(*s, dtype=torch.bfloat16) * 0.05)(Bsz, L, D)), 'log_A_real': _w((lambda *s: torch.randn(*s, dtype=torch.bfloat16) * 3.2)(D, N) * 0.5), 'A_imag': _w((lambda *s: torch.randn(*s, dtype=torch.bfloat16) * 0.1)(D, N) * 3.14), 'C_real': _w((lambda *s: torch.randn(*s, dtype=torch.bfloat16) * 0.4)(D, N) / N ** 0.5), 'C_imag': _w((lambda *s: torch.randn(*s, dtype=torch.bfloat16) * 0.4)(D, N) / N ** 0.5), 'log_dt': _w((lambda *s: torch.randn(*s, dtype=torch.bfloat16) * 0.1)(D) * 0.5 - 4.0), 'D_skip': _w((lambda *s: torch.randn(*s, dtype=torch.bfloat16) * 0.1)(D))}
    _A_in = _A_setup()

    def _B_setup():
        B, S, D, F = (1, 2048, 640, 1728)
        return {'x': _w((lambda *s: torch.randn(*s, dtype=torch.bfloat16) * 0.05)(B, S, D)), 'w_gate': _w((lambda *s: torch.randn(*s, dtype=torch.bfloat16) * 0.05)(D, F)), 'w_up': _w((lambda *s: torch.randn(*s, dtype=torch.bfloat16) * 0.05)(D, F)), 'w_down': _w((lambda *s: torch.randn(*s, dtype=torch.bfloat16) * 0.05)(F, D))}
    _B_in = _B_setup()
    return {'A_u': _A_in['u'], 'A_log_A_real': _A_in['log_A_real'], 'A_A_imag': _A_in['A_imag'], 'A_C_real': _A_in['C_real'], 'A_C_imag': _A_in['C_imag'], 'A_log_dt': _A_in['log_dt'], 'A_D_skip': _A_in['D_skip'], 'B_x': _B_in['x'], 'B_w_gate': _B_in['w_gate'], 'B_w_up': _B_in['w_up'], 'B_w_down': _B_in['w_down'], 'c': _w((lambda *s: torch.randn(*s, dtype=torch.bfloat16) * 0.1)(1, 640) * 8.0), 'w_mod': _w((lambda *s: torch.randn(*s, dtype=torch.bfloat16) * 0.1)(640, 6 * 640) * 640 ** (-0.5) * 8.0)}

def reference(A_u, A_log_A_real, A_A_imag, A_C_real, A_C_imag, A_log_dt, A_D_skip, B_x, B_w_gate, B_w_up, B_w_down, c, w_mod):

    def _A_ref(u, log_A_real, A_imag, C_real, C_imag, log_dt, D_skip):
        L = u.shape[1]
        dt = torch.exp(log_dt)
        A = -torch.exp(log_A_real) + 1j * A_imag
        C = (C_real + 1j * C_imag) * dt[:, None]
        pos = (lambda x, dt: x.to(dt))(torch.arange(L), log_dt.dtype)
        P = torch.exp((A * dt[:, None])[:, :, None] * pos[None, None, :])
        K = 2.0 * torch.einsum('dn,dnl->dl', C, P).real
        L2 = 2 * L
        u_t = (lambda x, *d: x.permute(*d))(u, 0, 2, 1)
        Kf = (lambda x, *a, **k: torch.fft.rfft(x.float(), *a, **k))(K, L2)
        Uf = (lambda x, *a, **k: torch.fft.rfft(x.float(), *a, **k))(u_t, L2)
        y = (lambda x, *a, **k: torch.fft.irfft(x, *a, **k).to(torch.bfloat16))(Uf * Kf[None, :, :], L2)[:, :, :L]
        y = (lambda x, *d: x.permute(*d))(y, 0, 2, 1)
        return y + u * D_skip[None, None, :]

    def _B_ref(x, w_gate, w_up, w_down):
        return _gelu(x @ w_gate) * (x @ w_up) @ w_down
    x = A_u
    mod = (_silu(c) @ w_mod).reshape(c.shape[0], 6, 1, -1)
    sa, ca, ga, sb, cb, gb = (mod[:, 0].clone(), mod[:, 1].clone(), mod[:, 2].clone(), mod[:, 3].clone(), mod[:, 4].clone(), mod[:, 5].clone())
    h = _layernorm(x, axis=-1) * (1 + ca) + sa
    x = x + ga * _A_ref(h, A_log_A_real, A_A_imag, A_C_real, A_C_imag, A_log_dt, A_D_skip)
    h = _layernorm(x, axis=-1) * (1 + cb) + sb
    x = x + gb * _B_ref(h, B_w_gate, B_w_up, B_w_down)
    return x
```

```cpp
#include <cuda_runtime.h>
#include <cuda.h>
#include <cuda_bf16.h>
#include <cuda_fp16.h>
#include <stdint.h>
#include <stddef.h>

typedef __nv_bfloat16 bf16;
constexpr int L = 2048, D = 640, F = 1728;

struct Scratch {
  unsigned char x1t[D * L * 2];
  unsigned char w1img[2 * D * F * 2];
  unsigned char w2img[216 * 10240];
  unsigned char actimg[16 * 216 * 2048];
  uint4 st1[16 * (L / 2)];
  uint4 st2[L / 2];
  float uv[4 * 2 * F * 2];
  unsigned modw[4 * 6 * D];
  unsigned cnt[(64 + 16 + 128) * 32];
  unsigned epoch[32];
  unsigned tsync[128];
};
__device__ __align__(1024) Scratch g_s;

struct Params {
  uint32_t zero; const bf16 *lar, *aim, *cre, *cim, *ldt;
  const bf16 *dsk, *c, *x, *wm; Scratch* s; const void* gtab; const bf16 *wg, *wu;
  const bf16* wd; bf16* out;
};

struct Maps { CUtensorMap x[2], wm, w[2], x1, res, w1[2], out; };

constexpr uint32_t SBC = 1024;
#define SB (SBC + ((blockIdx.x & 1) << 24))
constexpr uint32_t SM_X = 0, SM_W = 163840, SM_STG = SM_W + 51200;
constexpr uint32_t SM_UV = 225280, SM_ST = SM_UV + 1728, SM_WP = SM_ST + 1024, SM_GK = SM_WP + 1104, SM_GB = SM_WP, SM_CH = SM_WP + 1856, SM_BAR = SM_CH + 256;
constexpr int B_FW = 0  , B_UV = 234  , B_FLG = 80  , B_EW = 100  , B_DUMMY = 177, B_SG = 183  , B_PF = 188  , B_EB = 193  ,
              B_PE = 200  , B_HS = 205  , B_BOX = 210  , B_ROWS = 218, B_GT = 219, B_WM = 220  , B_RES = 224, B_AB = 225, B_ST = 226, B_WF = 227  ,
              B_PD = 77  , B_GB = 79, B_GA = 239, B_GO = 229, NBAR = 240;
constexpr uint32_t SM_DBG = SM_BAR + NBAR * 8, SM_TOTAL = SM_DBG + 256;
#define BAR (SB + SM_BAR)
constexpr uint32_t HO = 2240, A5 = 4480, A3 = 8064, A7 = 11648, A9 = 13696;
constexpr uint32_t SM_PART = 81920, PO = 2112, PSZ = 4160, PP2 = 7808, PP3 = 10944  , PBUF = 16384, SM_STG2 = 114688, XO = 4608, G2B = 20480;
constexpr uint32_t SM_BLK = 131072, PD1 = 1280, P5 = 2560, P3 = 3072, P7 = 3584, P9 = 4096, KV = 8192;
constexpr uint32_t SM_ROWS = 182272  , SM_WM = 202752, SM_GT = 223232  , SM_ROW = SM_WP + 0, SM_RED = SM_WP + 512, SM_SIL = SM_WP + 768;
#define blk(c) (SB + SM_BLK + (4 - (c)) * 10240)
#define NREP 2
constexpr int C_X1 = 0, C_W1 = 5 * 32, C_W2 = 10 * 32, C_REP = 16 * 32, C_ACT = 64 * 32, C_Q = 80 * 32;
constexpr int F_X1 = B_FLG, F_W1 = B_FLG + 5, F_Q = B_FLG + 10, F_W2 = B_FLG + 11, F_ACT = B_FLG + 13;
#define G2N 8
constexpr int B_FL = B_FW + 50, B_EL = B_EW + 50;
constexpr uint32_t G_RES = (27 % G2N) * 26624;
#define PFPOS 9
#define PFPOS2 9
#define R1GATE 1
#define X1FENCE 0
#define POLLACQ 0
#define EPIUNR_ 1
constexpr int EPIUNR = EPIUNR_;
#define CONVREG 208
#define MAP 0
#define RESGATE 5
#define QPAUSE 9
#define ARMD 1
#define NPOLL 3
#define POLLGAP 100
#define WPIECES 1
#define WINFL 1
#define LATEG F_X1+4
#define WGAP 250
#define BGATE B_HS
#define PERM 1
#define QMODE 0
#define SYNCG 32
#define SYNCAT (10 * SYNCT - 7)
#define SYNCD -100
#define SYNCP 640
#define SYNCK 15
#define SYNCT 4
#define STRICT 1
#define G2F 6
#define PACE 1500
#define HDEP 3
#define PSLEEP 300
#define G2U 1
#define AGATE B_BOX+7
#define LGATE B_AB
#define W2SPLIT 17
#define T0GATE B_PD
#define STAG 0
#define STAGO 0x01234
#define WMPOS 0
#define G2GATE 43
#define G2LEAD 0
__host__ __device__ constexpr int tcol(int tk) { return tk < 2 ? 48 * tk : 16 + 40 * tk; }

struct GTab { unsigned short o[576 * 4]; };
constexpr int kv_off(int p) {
  if (p == 0) return 64;
  const int A[8] = {8, 4, 264, 260, 520, 516, 776, 772}, B[8] = {258, 262, 2, 6, 1, 3, 5, 7};
  for (int c = 0; c < 8; c++) {
    if (p >= A[c] && p < A[c] + 256 && (p - A[c]) % 8 == 0) return c * 80 + (p - A[c]) / 4;
    if (p >= B[c] && p < B[c] + 256 && (p - B[c]) % 8 == 0) return (8 + c) * 80 + (p - B[c]) / 4;
    if (c % 2 == 0 && p >= A[c] + 1024 && p < A[c] + 1280 && (p - A[c]) % 8 == 0) return (16 + c) * 80 + (p - A[c] - 1024) / 4;
  }
  return -1;
}
constexpr int KV_ZERO = 66, KV_512 = kv_off(512), KV_1024 = kv_off(1024);
constexpr int rne_pos(int l) { const int r = l <= 256 ? 0 : (l <= 512 ? 1 : 2); return r == 0 ? l : ((l + (1 << (r - 1)) - 1 + ((l >> r) & 1)) >> r) << r; }
constexpr int tap_off(int tb, int hi, int l) {
  if (tb < 2) { const int seg = 2 * tb + hi; return (l >= 0 && l < (seg < 3 ? 128 : 131)) ? kv_off(rne_pos(128 * seg + l)) : KV_ZERO; }
  if (tb == 2) return (l >= 0 && l < 32) ? kv_off(8 * (65 + 32 * hi + l)) : KV_ZERO;
  if (tb == 3) return (l >= 0 && l < 32) ? kv_off(8 * (64 + 32 * hi + l) + 4) : ((hi && l == 32) ? kv_off(1024) : KV_ZERO);
  const int u = l + 32 * hi;
  return (u >= 0 && u < 64) ? kv_off(8 * (125 + tb + 2 * u)) : KV_ZERO;
}
constexpr GTab make_gtab() {
  GTab t = {};
  for (int e = 0; e < 576; e++) {
    const int tb = e < 320 ? e / 160 : 2 + (e - 320) / 64, l = e < 320 ? e % 160 - 16 : (e - 320) % 64 - (tb < 4 ? 16 : 32), st = (tb == 2 || tb == 3) ? 2 : 1;
    for (int k = 0; k < 4; k++) t.o[4 * e + k] = (unsigned short)tap_off(tb, k >> 1, l - (k & 1) * st);
  }
  return t;
}
__device__ const __align__(128) GTab g_gtab = make_gtab();

#define DI __device__ __forceinline__
DI uint32_t smem_u32(const void* p) { return (uint32_t)__cvta_generic_to_shared(p); }
DI void mbar_init_elect(uint32_t a, uint32_t c) { asm volatile("{.reg .pred p; elect.sync _|p, 0xffffffff;\n@p mbarrier.init.shared::cta.b64 [%0], %1;}" ::"r"(a), "r"(c) : "memory"); }
DI void mbar_init10(uint32_t a, uint32_t c) {
  asm volatile("{.reg .pred p; elect.sync _|p, 0xffffffff;\n"
               "@p mbarrier.init.shared::cta.b64 [%0], %1; @p mbarrier.init.shared::cta.b64 [%0 + 8], %1; @p mbarrier.init.shared::cta.b64 [%0 + 16], %1;\n"
               "@p mbarrier.init.shared::cta.b64 [%0 + 24], %1; @p mbarrier.init.shared::cta.b64 [%0 + 32], %1; @p mbarrier.init.shared::cta.b64 [%0 + 40], %1;\n"
               "@p mbarrier.init.shared::cta.b64 [%0 + 48], %1; @p mbarrier.init.shared::cta.b64 [%0 + 56], %1; @p mbarrier.init.shared::cta.b64 [%0 + 64], %1;\n"
               "@p mbarrier.init.shared::cta.b64 [%0 + 72], %1;\nfence.mbarrier_init.release.cluster;}" ::"r"(a), "r"(c) : "memory");
}
DI void mbar_expect(uint32_t a, uint32_t b) { asm volatile("mbarrier.arrive.expect_tx.shared::cta.b64 _, [%0], %1;" ::"r"(a), "r"(b) : "memory"); }
DI void mbar_expect_if(bool c, uint32_t a, uint32_t b) { asm volatile("{.reg .pred p; setp.ne.u32 p, %2, 0;\n@p mbarrier.arrive.expect_tx.shared::cta.b64 _, [%0], %1;}" ::"r"(a), "r"(b), "r"((uint32_t)c) : "memory"); }
DI void mbar_arrive(uint32_t a) { asm volatile("mbarrier.arrive.shared::cta.b64 _, [%0];" ::"r"(a) : "memory"); }
DI void mbar_arrive_elect(uint32_t a) { asm volatile("{.reg .pred p; elect.sync _|p, 0xffffffff;\n@p mbarrier.arrive.shared::cta.b64 _, [%0];}" ::"r"(a) : "memory"); }
DI void mbar_wait(uint32_t a) {
  asm volatile("{.reg .pred p;\nLOOP: mbarrier.try_wait.parity.shared::cta.b64 p, [%0], 0;\n@!p bra.uni LOOP;}" ::"r"(a) : "memory");
}
#define rk(a) (a)
DI void bulk_g2s_elect(uint32_t dst, const void* src, uint32_t n, uint32_t bar) {
  asm volatile("{.reg .pred p; elect.sync _|p, 0xffffffff;\n"
               "@p cp.async.bulk.shared::cluster.global.mbarrier::complete_tx::bytes [%0], [%1], %2, [%3];}" ::"r"(rk(dst)), "l"(src), "r"(n), "r"(rk(bar)) : "memory");
}
DI void l2_prefetch_elect(const void* p, uint32_t n) { asm volatile("{.reg .pred p; elect.sync _|p, 0xffffffff;\n@p cp.async.bulk.prefetch.L2.global [%0], %1;}" ::"l"(p), "r"(n) : "memory"); }
DI void tma4d_elect(uint32_t dst, const CUtensorMap* map, int x, int y, int z, int u, uint32_t bar) {
  asm volatile("{.reg .pred p; elect.sync _|p, 0xffffffff;\n"
               "@p cp.async.bulk.tensor.4d.shared::cluster.global.mbarrier::complete_tx::bytes [%0], [%1, {%3, %4, %5, %6}], [%2];}" ::"r"(rk(dst)), "l"(map), "r"(rk(bar)), "r"(x), "r"(y), "r"(z), "r"(u) : "memory");
}
DI void tma5d_elect(uint32_t dst, const CUtensorMap* map, int x, int z, int v, int u, uint32_t bar) {
  asm volatile("{.reg .pred p; elect.sync _|p, 0xffffffff;\n"
               "@p cp.async.bulk.tensor.5d.shared::cluster.global.mbarrier::complete_tx::bytes [%0], [%1, {%3, 0, %4, %5, %6}], [%2];}" ::"r"(rk(dst)), "l"(map), "r"(rk(bar)), "r"(x), "r"(z), "r"(v), "r"(u) : "memory");
}
DI void tma2d_pf_elect(const CUtensorMap* map, int x, int y) {
  asm volatile("{.reg .pred p; elect.sync _|p, 0xffffffff;\n@p cp.async.bulk.prefetch.tensor.2d.L2.global [%0, {%1, %2}];}" ::"l"(map), "r"(x), "r"(y) : "memory");
}
DI void tma2d_elect(uint32_t dst, const CUtensorMap* map, int x, int y, uint32_t bar) {
  asm volatile("{.reg .pred p; elect.sync _|p, 0xffffffff;\n"
               "@p cp.async.bulk.tensor.2d.shared::cluster.global.mbarrier::complete_tx::bytes [%0], [%1, {%3, %4}], [%2];}" ::"r"(rk(dst)), "l"(map), "r"(rk(bar)), "r"(x), "r"(y) : "memory");
}
DI void bar_sync(int id, int n) { asm volatile("bar.sync %0, %1;" ::"r"(id), "r"(n) : "memory"); }
DI void bar_arrive(int id, int n) { asm volatile("bar.arrive %0, %1;" ::"r"(id), "r"(n) : "memory"); }
DI void proxy_fence_smem() { asm volatile("fence.proxy.async.shared::cta;" ::: "memory"); }
DI void publish(unsigned* c) { asm volatile("fence.proxy.async.global;\nfence.acq_rel.gpu;\nred.relaxed.gpu.global.add.u32 [%0], 1;" ::"l"(c) : "memory"); }
DI void bulk_s2g(void* dst, uint32_t src, uint32_t n) { asm volatile("cp.async.bulk.global.shared::cta.bulk_group [%0], [%1], %2;" ::"l"(dst), "r"(rk(src)), "r"(n) : "memory"); }
template <int R = 1> DI void publish_bulk(unsigned* c) {
  asm volatile("cp.async.bulk.commit_group;\ncp.async.bulk.wait_group 0;" ::: "memory");
#pragma unroll
  for (int i = 0; i < R; i++) asm volatile("cp.reduce.async.bulk.global.shared::cta.bulk_group.add.u32 [%0], [%1], 16;" ::"l"(c + i * C_REP), "r"(rk(SB + SM_CH + 224)) : "memory");
  asm volatile("cp.async.bulk.commit_group;" ::: "memory");
}
DI void wg_fence() { asm volatile("wgmma.fence.sync.aligned;" ::: "memory"); }
DI void wg_commit() { asm volatile("wgmma.commit_group.sync.aligned;" ::: "memory"); }
template <int N> DI void wg_wait() { asm volatile("wgmma.wait_group.sync.aligned %0;" ::"n"(N) : "memory"); }
template <int N> DI void reg_inc() { asm volatile("setmaxnreg.inc.sync.aligned.u32 %0;" ::"n"(N)); }
template <int N> DI void reg_dec() { asm volatile("setmaxnreg.dec.sync.aligned.u32 %0;" ::"n"(N)); }
DI uint32_t pack_bf16(float lo, float hi) { uint32_t r; asm("cvt.rn.bf16x2.f32 %0, %1, %2;" : "=r"(r) : "f"(hi), "f"(lo)); return r; }
DI uint32_t pack_f16(float lo, float hi) { uint32_t r; asm("cvt.rn.f16x2.f32 %0, %1, %2;" : "=r"(r) : "f"(hi), "f"(lo)); return r; }
DI float bf_lo(uint32_t v) { return __uint_as_float(v << 16); }
DI float bf_hi(uint32_t v) { return __uint_as_float(v & 0xffff0000u); }
DI float bfr(float x) { return __uint_as_float(pack_bf16(0.f, x)); }
DI float ldbf(const bf16* p) { return __uint_as_float((uint32_t)__ldg((const unsigned short*)p) << 16); }
DI __half2 H2(uint32_t v) { return *reinterpret_cast<__half2*>(&v); }
DI uint32_t U(__half2 v) { return *reinterpret_cast<uint32_t*>(&v); }
DI uint32_t hadd(uint32_t a, uint32_t b) { return U(__hadd2(H2(a), H2(b))); }
DI uint32_t hfma(uint32_t a, uint32_t b, uint32_t c) { return U(__hfma2(H2(a), H2(b), H2(c))); }
DI uint32_t bfma(uint32_t a, uint32_t b, uint32_t c) { uint32_t r; asm("fma.rn.bf16x2 %0, %1, %2, %3;" : "=r"(r) : "r"(a), "r"(b), "r"(c)); return r; }
DI uint32_t bmul(uint32_t a, uint32_t b) { uint32_t r; asm("mul.rn.bf16x2 %0, %1, %2;" : "=r"(r) : "r"(a), "r"(b)); return r; }
DI uint32_t uv_word(float v, uint32_t lo) { const uint32_t b = __float_as_uint(v), a = b & 0x7fffffffu; return (b & 0x80000000u) | ((max(a + 0x8000u, lo) - lo) & 0x7fff0000u) | lo; }
DI float tanh_fast(float x) { float r; asm("tanh.approx.f32 %0, %1;" : "=f"(r) : "f"(x)); return r; }
DI float pow2_inv(float x) { return __uint_as_float((253u - min(__float_as_uint(x) >> 23, 252u)) << 23); }
DI unsigned ld_relaxed(const unsigned* p) { unsigned v; asm volatile("ld.relaxed.gpu.global.u32 %0, [%1];" : "=r"(v) : "l"(p) : "memory"); return v; }
DI unsigned ld_acquire(const unsigned* p) { unsigned v; asm volatile("ld.acquire.gpu.global.u32 %0, [%1];" : "=r"(v) : "l"(p) : "memory"); return v; }
DI void st_relaxed(unsigned* p, unsigned v) { asm volatile("st.relaxed.gpu.global.u32 [%0], %1;" ::"l"(p), "r"(v) : "memory"); }
DI float rsq(float x) { float r; asm("rsqrt.approx.ftz.f32 %0, %1;" : "=f"(r) : "f"(x)); return r; }
DI uint4 ld_relaxed4(const void* p) { uint4 v; asm volatile("ld.relaxed.gpu.global.v4.u32 {%0,%1,%2,%3}, [%4];" : "=r"(v.x), "=r"(v.y), "=r"(v.z), "=r"(v.w) : "l"(p) : "memory"); return v; }
DI uint4 ldg4(const void* p) { uint4 v; asm volatile("ld.global.nc.L1::no_allocate.v4.u32 {%0,%1,%2,%3}, [%4];" : "=r"(v.x), "=r"(v.y), "=r"(v.z), "=r"(v.w) : "l"(p)); return v; }
template <int N> DI void poll_mod(float (&o)[N], const unsigned* p, int stride, uint32_t epoch) {
  uint32_t v[N][4], bad; int it = 0;
  do {
    bad = 0;
#pragma unroll
    for (int i = 0; i < N; i++)
#pragma unroll
      for (int k = 0; k < 4; k++) v[i][k] = ld_relaxed(p + i * stride + k * (6 * D));
#pragma unroll
    for (int i = 0; i < N; i++) bad |= (v[i][0] ^ epoch) | (v[i][1] ^ epoch) | (v[i][2] ^ epoch) | (v[i][3] ^ epoch);
  } while ((bad & 63u) && ++it < 100000);
#pragma unroll
  for (int i = 0; i < N; i++) o[i] = bfr((__uint_as_float(v[i][0]) + __uint_as_float(v[i][1])) + (__uint_as_float(v[i][2]) + __uint_as_float(v[i][3])));
}
DI void poll_mod2(float (&o)[2], const unsigned* p, uint32_t epoch) {
  uint2 v[4]; uint32_t bad; int it = 0;
  do {
    bad = 0;
#pragma unroll
    for (int k = 0; k < 4; k++) asm volatile("ld.relaxed.gpu.global.v2.u32 {%0,%1}, [%2];" : "=r"(v[k].x), "=r"(v[k].y) : "l"(p + k * (6 * D)) : "memory");
#pragma unroll
    for (int k = 0; k < 4; k++) bad |= (v[k].x ^ epoch) | (v[k].y ^ epoch);
  } while ((bad & 63u) && ++it < 100000);
  o[0] = bfr((__uint_as_float(v[0].x) + __uint_as_float(v[1].x)) + (__uint_as_float(v[2].x) + __uint_as_float(v[3].x)));
  o[1] = bfr((__uint_as_float(v[0].y) + __uint_as_float(v[1].y)) + (__uint_as_float(v[2].y) + __uint_as_float(v[3].y)));
}
DI void st_relaxed2(float* p, unsigned a, float b) { asm volatile("st.relaxed.gpu.global.v2.u32 [%0], {%1,%2};" ::"l"(p), "r"(a), "f"(b) : "memory"); }
DI void l2_pf_if(bool c, const void* p) { asm volatile("{.reg .pred p; setp.ne.u32 p, %1, 0;\n@p prefetch.global.L2 [%0];}" ::"l"(p), "r"((uint32_t)c)); }
DI float ex2(float x) { float r; asm("ex2.approx.ftz.f32 %0, %1;" : "=f"(r) : "f"(x)); return r; }
DI float rcp(float x) { float r; asm("rcp.approx.ftz.f32 %0, %1;" : "=f"(r) : "f"(x)); return r; }
DI void l2_pf(const void* p) { asm volatile("prefetch.global.L2 [%0];" ::"l"(p)); }
DI uint32_t lds16(uint32_t a) { uint32_t v; asm volatile("ld.shared.u16 %0, [%1];" : "=r"(v) : "r"(a)); return v; }
DI uint32_t lds32(uint32_t a) { uint32_t v; asm volatile("ld.shared.u32 %0, [%1];" : "=r"(v) : "r"(a)); return v; }
DI float ldsf(uint32_t a) { return __uint_as_float(lds32(a)); }
DI void lds64(uint32_t& x, uint32_t& y, uint32_t a) { asm volatile("ld.shared.v2.u32 {%0,%1}, [%2];" : "=r"(x), "=r"(y) : "r"(a)); }
DI void lds64_if(bool c, uint32_t& x, uint32_t& y, uint32_t a) { asm volatile("{.reg .pred p; setp.ne.u32 p, %3, 0;\n@p ld.shared.v2.u32 {%0,%1}, [%2];}" : "+r"(x), "+r"(y) : "r"(a), "r"((uint32_t)c)); }
DI uint4 lds128(uint32_t a) { uint4 v; asm volatile("ld.shared.v4.u32 {%0,%1,%2,%3}, [%4];" : "=r"(v.x), "=r"(v.y), "=r"(v.z), "=r"(v.w) : "r"(a)); return v; }
DI void sts16(uint32_t a, uint32_t v) { asm volatile("st.shared.u16 [%0], %1;" ::"r"(a), "h"((unsigned short)v)); }
DI void sts32(uint32_t a, uint32_t v) { asm volatile("st.shared.u32 [%0], %1;" ::"r"(a), "r"(v)); }
DI void stsf(uint32_t a, float v) { sts32(a, __float_as_uint(v)); }
DI void sts64(uint32_t a, uint32_t x, uint32_t y) { asm volatile("st.shared.v2.u32 [%0], {%1,%2};" ::"r"(a), "r"(x), "r"(y)); }
DI void sts128(uint32_t a, uint32_t x, uint32_t y, uint32_t z, uint32_t w) { asm volatile("st.shared.v4.u32 [%0], {%1,%2,%3,%4};" ::"r"(a), "r"(x), "r"(y), "r"(z), "r"(w)); }
DI void ldsm4t(uint32_t (&r)[4], uint32_t a) { asm volatile("ldmatrix.sync.aligned.m8n8.x4.trans.shared.b16 {%0,%1,%2,%3}, [%4];" : "=r"(r[0]), "=r"(r[1]), "=r"(r[2]), "=r"(r[3]) : "r"(a)); }
DI void stsm4(uint32_t a, uint32_t x, uint32_t y, uint32_t z, uint32_t w) { asm volatile("stmatrix.sync.aligned.m8n8.x4.shared.b16 [%0], {%1,%2,%3,%4};" ::"r"(a), "r"(x), "r"(y), "r"(z), "r"(w)); }
DI void stsm2(uint32_t a, uint32_t x, uint32_t y) { asm volatile("stmatrix.sync.aligned.m8n8.x2.shared.b16 [%0], {%1,%2};" ::"r"(a), "r"(x), "r"(y)); }
DI void stsm4t(uint32_t a, uint32_t x, uint32_t y, uint32_t z, uint32_t w) { asm volatile("stmatrix.sync.aligned.m8n8.x4.trans.shared.b16 [%0], {%1,%2,%3,%4};" ::"r"(a), "r"(x), "r"(y), "r"(z), "r"(w)); }
DI uint32_t movm(uint32_t a) { uint32_t d; asm volatile("movmatrix.sync.aligned.m8n8.trans.b16 %0, %1;" : "=r"(d) : "r"(a)); return d; }
DI void mma_f16(uint32_t (&c)[2], const uint32_t (&a)[4], uint32_t b0, uint32_t b1) {
  asm volatile("mma.sync.aligned.m16n8k16.row.col.f16.f16.f16.f16 {%0,%1},{%2,%3,%4,%5},{%6,%7},{%0,%1};" : "+r"(c[0]), "+r"(c[1]) : "r"(a[0]), "r"(a[1]), "r"(a[2]), "r"(a[3]), "r"(b0), "r"(b1));
}
DI void mma_bf16(float (&c)[4], uint32_t a0, uint32_t a1, uint32_t a2, uint32_t a3, uint32_t b0, uint32_t b1) {
  asm volatile("mma.sync.aligned.m16n8k16.row.col.f32.bf16.bf16.f32 {%0,%1,%2,%3},{%4,%5,%6,%7},{%8,%9},{%0,%1,%2,%3};" : "+f"(c[0]), "+f"(c[1]), "+f"(c[2]), "+f"(c[3]) : "r"(a0), "r"(a1), "r"(a2), "r"(a3), "r"(b0), "r"(b1));
}
DI uint32_t wsel(const uint4& v, int i) { return i == 0 ? v.x : (i == 1 ? v.y : (i == 2 ? v.z : v.w)); }
DI void ldsm4(uint32_t (&r)[4], uint32_t a) { asm volatile("ldmatrix.sync.aligned.m8n8.x4.shared.b16 {%0,%1,%2,%3}, [%4];" : "=r"(r[0]), "=r"(r[1]), "=r"(r[2]), "=r"(r[3]) : "r"(a)); }
template <int N> DI void reg_fence(float (&d)[N]) {
#pragma unroll
  for (int i = 0; i < N; i++) asm volatile("" : "+f"(d[i])::"memory");
}
template <int N> DI void reg_fence(uint32_t (&d)[N]) {
#pragma unroll
  for (int i = 0; i < N; i++) asm volatile("" : "+r"(d[i])::"memory");
}
template<int TA,int TB,uint32_t HA,uint32_t HB,int ARR> __device__ __forceinline__ void wgmma_n8(float (&d)[ARR], uint32_t la, uint32_t lb, int sd){
  asm volatile("{.reg .pred p; .reg .b64 da, db; setp.ne.b32 p, %6, 0; mov.b64 da, {%4, %9}; mov.b64 db, {%5, %10};\n"
  "wgmma.mma_async.sync.aligned.m64n8k16.f32.bf16.bf16 {%0,%1,%2,%3}, da, db, p, 1, 1, %7, %8;}"
  : "+f"(d[0]),"+f"(d[1]),"+f"(d[2]),"+f"(d[3])
  : "r"(la), "r"(lb), "r"(sd), "n"(TA), "n"(TB), "n"(HA), "n"(HB));
}
template<int TA,int TB,uint32_t HA,uint32_t HB,int ARR> __device__ __forceinline__ void wgmma_n80(float (&d)[ARR], uint32_t la, uint32_t lb, int sd){
  asm volatile("{.reg .pred p; .reg .b64 da, db; setp.ne.b32 p, %42, 0; mov.b64 da, {%40, %45}; mov.b64 db, {%41, %46};\n"
  "wgmma.mma_async.sync.aligned.m64n80k16.f32.bf16.bf16 {%0,%1,%2,%3,%4,%5,%6,%7,%8,%9,%10,%11,%12,%13,%14,%15,%16,%17,%18,%19,%20,%21,%22,%23,%24,%25,%26,%27,%28,%29,%30,%31,%32,%33,%34,%35,%36,%37,%38,%39}, da, db, p, 1, 1, %43, %44;}"
  : "+f"(d[0]),"+f"(d[1]),"+f"(d[2]),"+f"(d[3]),"+f"(d[4]),"+f"(d[5]),"+f"(d[6]),"+f"(d[7]),"+f"(d[8]),"+f"(d[9]),"+f"(d[10]),"+f"(d[11]),"+f"(d[12]),"+f"(d[13]),"+f"(d[14]),"+f"(d[15]),"+f"(d[16]),"+f"(d[17]),"+f"(d[18]),"+f"(d[19]),"+f"(d[20]),"+f"(d[21]),"+f"(d[22]),"+f"(d[23]),"+f"(d[24]),"+f"(d[25]),"+f"(d[26]),"+f"(d[27]),"+f"(d[28]),"+f"(d[29]),"+f"(d[30]),"+f"(d[31]),"+f"(d[32]),"+f"(d[33]),"+f"(d[34]),"+f"(d[35]),"+f"(d[36]),"+f"(d[37]),"+f"(d[38]),"+f"(d[39])
  : "r"(la), "r"(lb), "r"(sd), "n"(TA), "n"(TB), "n"(HA), "n"(HB));
}
template<int TA,int TB,uint32_t HA,uint32_t HB,int ARR> __device__ __forceinline__ void wgmma_n96(float (&d)[ARR], uint32_t la, uint32_t lb, int sd){
  asm volatile("{.reg .pred p; .reg .b64 da, db; setp.ne.b32 p, %50, 0; mov.b64 da, {%48, %53}; mov.b64 db, {%49, %54};\n"
  "wgmma.mma_async.sync.aligned.m64n96k16.f32.bf16.bf16 {%0,%1,%2,%3,%4,%5,%6,%7,%8,%9,%10,%11,%12,%13,%14,%15,%16,%17,%18,%19,%20,%21,%22,%23,%24,%25,%26,%27,%28,%29,%30,%31,%32,%33,%34,%35,%36,%37,%38,%39,%40,%41,%42,%43,%44,%45,%46,%47}, da, db, p, 1, 1, %51, %52;}"
  : "+f"(d[0]),"+f"(d[1]),"+f"(d[2]),"+f"(d[3]),"+f"(d[4]),"+f"(d[5]),"+f"(d[6]),"+f"(d[7]),"+f"(d[8]),"+f"(d[9]),"+f"(d[10]),"+f"(d[11]),"+f"(d[12]),"+f"(d[13]),"+f"(d[14]),"+f"(d[15]),"+f"(d[16]),"+f"(d[17]),"+f"(d[18]),"+f"(d[19]),"+f"(d[20]),"+f"(d[21]),"+f"(d[22]),"+f"(d[23]),"+f"(d[24]),"+f"(d[25]),"+f"(d[26]),"+f"(d[27]),"+f"(d[28]),"+f"(d[29]),"+f"(d[30]),"+f"(d[31]),"+f"(d[32]),"+f"(d[33]),"+f"(d[34]),"+f"(d[35]),"+f"(d[36]),"+f"(d[37]),"+f"(d[38]),"+f"(d[39]),"+f"(d[40]),"+f"(d[41]),"+f"(d[42]),"+f"(d[43]),"+f"(d[44]),"+f"(d[45]),"+f"(d[46]),"+f"(d[47])
  : "r"(la), "r"(lb), "r"(sd), "n"(TA), "n"(TB), "n"(HA), "n"(HB));
}
template<int TB,uint32_t HB,int SD> __device__ __forceinline__ void wgmma_h128(uint32_t (&d)[32], const uint32_t (&a)[4], uint32_t lb){
  asm volatile("{.reg .pred p; .reg .b64 db; setp.ne.b32 p, %39, 0; mov.b64 db, {%36, %38};\n"
  "wgmma.mma_async.sync.aligned.m64n128k16.f16.f16.f16 {%0,%1,%2,%3,%4,%5,%6,%7,%8,%9,%10,%11,%12,%13,%14,%15,%16,%17,%18,%19,%20,%21,%22,%23,%24,%25,%26,%27,%28,%29,%30,%31}, {%32,%33,%34,%35}, db, p, 1, 1, %37;}"
  : "+r"(d[0]),"+r"(d[1]),"+r"(d[2]),"+r"(d[3]),"+r"(d[4]),"+r"(d[5]),"+r"(d[6]),"+r"(d[7]),"+r"(d[8]),"+r"(d[9]),"+r"(d[10]),"+r"(d[11]),"+r"(d[12]),"+r"(d[13]),"+r"(d[14]),"+r"(d[15]),"+r"(d[16]),"+r"(d[17]),"+r"(d[18]),"+r"(d[19]),"+r"(d[20]),"+r"(d[21]),"+r"(d[22]),"+r"(d[23]),"+r"(d[24]),"+r"(d[25]),"+r"(d[26]),"+r"(d[27]),"+r"(d[28]),"+r"(d[29]),"+r"(d[30]),"+r"(d[31])
  : "r"(a[0]), "r"(a[1]), "r"(a[2]), "r"(a[3]), "r"(lb), "n"(TB), "n"(HB), "n"(SD));
}
template<int TB,uint32_t HB,int SD> __device__ __forceinline__ void wgmma_h48(uint32_t (&d)[12], const uint32_t (&a)[4], uint32_t lb){
  asm volatile("{.reg .pred p; .reg .b64 db; setp.ne.b32 p, %19, 0; mov.b64 db, {%16, %18};\n"
  "wgmma.mma_async.sync.aligned.m64n48k16.f16.f16.f16 {%0,%1,%2,%3,%4,%5,%6,%7,%8,%9,%10,%11}, {%12,%13,%14,%15}, db, p, 1, 1, %17;}"
  : "+r"(d[0]),"+r"(d[1]),"+r"(d[2]),"+r"(d[3]),"+r"(d[4]),"+r"(d[5]),"+r"(d[6]),"+r"(d[7]),"+r"(d[8]),"+r"(d[9]),"+r"(d[10]),"+r"(d[11])
  : "r"(a[0]), "r"(a[1]), "r"(a[2]), "r"(a[3]), "r"(lb), "n"(TB), "n"(HB), "n"(SD));
}
template<int TB,uint32_t HB,int SD> __device__ __forceinline__ void wgmma_h32(uint32_t (&d)[8], const uint32_t (&a)[4], uint32_t lb){
  asm volatile("{.reg .pred p; .reg .b64 db; setp.ne.b32 p, %15, 0; mov.b64 db, {%12, %14};\n"
  "wgmma.mma_async.sync.aligned.m64n32k16.f16.f16.f16 {%0,%1,%2,%3,%4,%5,%6,%7}, {%8,%9,%10,%11}, db, p, 1, 1, %13;}"
  : "+r"(d[0]),"+r"(d[1]),"+r"(d[2]),"+r"(d[3]),"+r"(d[4]),"+r"(d[5]),"+r"(d[6]),"+r"(d[7])
  : "r"(a[0]), "r"(a[1]), "r"(a[2]), "r"(a[3]), "r"(lb), "n"(TB), "n"(HB), "n"(SD));
}

__host__ __device__ constexpr uint32_t dlo(uint32_t off, uint32_t lbo) { return ((SBC + off) >> 4) | ((lbo >> 4) << 16); }
__host__ __device__ constexpr uint32_t dhi(uint32_t sbo, uint32_t sw) { return (sbo >> 4) | (sw << 30); }

#define CT(i)
#define CT0(i)
#define BOXP(i)
#define CT2(i)
#define CT2B(i)

DI int fresh_tid() { int t; asm volatile("mov.u32 %0, %tid.x;\nadd.u32 %0, %0, %1;" : "=r"(t) : "r"(lds32(SB + SM_CH + 252))); return t; }
#define ROLE_IDS const int tid = fresh_tid(), lane = tid & 31, g = lane >> 2, q = lane & 3, t = tid & 127, w = __shfl_sync(~0u, t >> 5, 0); \
  const uint32_t epoch = lds32(SB + SM_CH + 248); (void)g; (void)q; (void)epoch; (void)w;

struct cf { float x, y; };
DI cf cmul(cf a, cf b) { return {fmaf(a.x, b.x, -a.y * b.y), fmaf(a.x, b.y, a.y * b.x)}; }
DI cf csq(cf a) { return {fmaf(a.x, a.x, -a.y * a.y), 2.f * a.x * a.y}; }
DI cf cpow(float a2, float br, float p) {
  const float m = ex2(a2 * p), f = fmaf(br, p, -__fadd_rn(fmaf(br, p, 12582912.f), -12582912.f)) * 6.283185307f;
  return {m * __cosf(f), m * __sinf(f)};
}
DI void hcmul(uint32_t& o_r, uint32_t& o_i, uint32_t r, uint32_t i, __half2 er, __half2 ei) {
  o_r = U(__hfma2(H2(r), er, __hmul2(H2(i), __hneg2(ei))));
  o_i = U(__hfma2(H2(i), er, __hmul2(H2(r), ei)));
}

template <int LB> DI void unit_gemv(float (&acc)[4], uint32_t ua, uint32_t vo) {
  wg_fence();
#pragma unroll
  for (int s = 0; s < 10; s++) wgmma_n8<1, 0, dhi(1024, 1), dhi(128, 0)>(acc, ua + s * 128, dlo(vo, LB) + s * (LB / 8), s != 0);
  wg_commit();
  wg_wait<0>();
  reg_fence(acc);
}
DI void box_sums(int task, int lane) {
    const int c = task / 3, Q = task - 3 * c, n = 32 * Q + lane;
    const uint32_t sg = SB + c * 16384;
    uint32_t e[13];
    lds64(e[0], e[1], sg + 120 + n * 16);
    { const uint4 p = lds128(sg + HO + 112 + n * 16); e[2] = p.x; e[3] = p.y; e[4] = p.z; e[5] = p.w; }
    { const uint4 p = lds128(sg + 128 + n * 16); e[6] = p.x; e[7] = p.y; e[8] = p.z; e[9] = p.w; }
    { const uint4 p = lds128(sg + HO + 128 + n * 16); e[10] = p.x; e[11] = p.y; e[12] = p.z; }
    uint32_t o[12], s[12], tt[10], b3[11], b5[9];
#pragma unroll
    for (int k = 0; k < 12; k++) { o[k] = __byte_perm(e[k], e[k + 1], 0x5432); s[k] = hadd(e[k], o[k]); }
#pragma unroll
    for (int k = 0; k < 10; k++) tt[k] = hadd(s[k], s[k + 1]);
#pragma unroll
    for (int k = 0; k < 11; k++) b3[k] = hadd(o[k], s[k + 1]);
#pragma unroll
    for (int k = 0; k < 9; k++) b5[k] = hadd(tt[k + 1], e[k + 3]);
    const uint32_t a2_ = sg + 512 + (n >> 3) * 256 + (n & 7) * 16;
    sts128(a2_ + A3, b3[3], b3[4], b3[5], b3[6]); sts128(a2_ + A3 + 128, b3[7], b3[8], b3[9], b3[10]);
    sts128(a2_ + A5, b5[0], b5[1], b5[2], b5[3]); sts128(a2_ + A5 + 128, b5[4], b5[5], b5[6], b5[7]);
    if (Q < 2) {
      const uint32_t a = Q * 1024 + lane * 16;
      sts128(sg + A7 + a, hadd(b3[0], tt[2]), hadd(b3[1], tt[3]), hadd(b3[2], tt[4]), hadd(b3[3], tt[5]));
      sts128(sg + A7 + a + 512, hadd(b3[4], tt[6]), hadd(b3[5], tt[7]), hadd(b3[6], tt[8]), hadd(b3[7], tt[9]));
      sts128(sg + A9 + a + 512, hadd(tt[0], b5[1]), hadd(tt[1], b5[2]), hadd(tt[2], b5[3]), hadd(tt[3], b5[4]));
      if (n < 63) sts128(sg + A9 + ((n + 1) >> 5) * 1024 + ((n + 1) & 31) * 16, hadd(tt[4], b5[5]), hadd(tt[5], b5[6]), hadd(tt[6], b5[7]), hadd(tt[7], b5[8]));
    }
    __syncwarp();
    if (lane < (Q == 0 ? 2 : 1)) mbar_arrive(BAR + (B_SG + c) * 8);
  }

DI void poll_flags(const Params& P, uint32_t todo, int cta, int m, int fid, int lane, int w, uint32_t epoch) {
  const unsigned* c = P.s->cnt + (lane < 10 ? 32 * lane + (cta % NREP) * C_REP : (lane < 13 ? C_W2 + 32 * (lane - 11) : C_ACT + m * 32 + 4 * (lane - 13)));
  const uint32_t target = epoch * (lane < 5 ? 128 : (lane < 7 ? 48 : (lane < 10 ? 40 : (lane < 13 ? 4 : 8))));
  const uint32_t me = 1u << lane, arm = me | (lane == 12 ? 1u << 14 : (lane == 11 ? 1u << 13 : (lane < 5 ? me >> ARMD : 0)));
  __nanosleep(w * POLLGAP);
#pragma unroll 1
  for (int it = 0; todo; it++) {
    bool hit = false;
    if ((todo & arm) == me) hit = (int)(ld_relaxed(c) - target) >= 0 || it > 100000;
    asm volatile("{.reg .pred p; setp.ne.u32 p, %1, 0;\n@p mbarrier.arrive.shared::cta.b64 _, [%0];}" ::"r"(BAR + (B_FLG + lane) * 8), "r"((uint32_t)hit) : "memory");
    todo &= ~__ballot_sync(~0u, hit);
    if (PSLEEP && todo > 0x7f) __nanosleep(PSLEEP);
  }
}

template <int TW>
DI void gemm1_task(float (&a0)[48], float (&a1)[48], int task) {
  constexpr uint32_t b0 = dlo(SM_W, 128);
  uint32_t bt = BAR + task * 80;
  uint32_t b = b0 + (TW == 48 ? 0 : ((0x240 >> (4 * task - 8)) & 7) * 640), a = dlo(SM_X, 0);
#pragma unroll 1
  for (int kc = 0; kc < 10; kc++) {
    mbar_wait(bt + B_FW * 8);
    wg_fence();
#pragma unroll
    for (int k = 0; k < 4; k++) {
      if (TW == 48) {
        wgmma_n96<1, 1, dhi(1024, 1), dhi(512, 0)>(a0, a + k * 128, b + (k >> 1) * (TW * 8) + (k & 1) * 16, (kc | k) != 0);
        wgmma_n96<1, 1, dhi(1024, 1), dhi(512, 0)>(a1, a + k * 128 + 512, b + (k >> 1) * (TW * 8) + (k & 1) * 16, (kc | k) != 0);
      } else {
        wgmma_n80<1, 1, dhi(1024, 1), dhi(512, 0)>(a0, a + k * 128, b + (k >> 1) * (TW * 8) + (k & 1) * 16, (kc | k) != 0);
        wgmma_n80<1, 1, dhi(1024, 1), dhi(512, 0)>(a1, a + k * 128 + 512, b + (k >> 1) * (TW * 8) + (k & 1) * 16, (kc | k) != 0);
      }
    }
    wg_commit();
    a += 1024; b += TW * 16; if (b == b0 + 3840) b = b0;
    bt += 8;
    wg_wait<1>();
    mbar_arrive_elect(kc > 0 ? bt + (B_EW - 2) * 8 : BAR + B_DUMMY * 8);
  }
  wg_wait<0>();
  reg_fence(a0); reg_fence(a1);
  mbar_arrive_elect(bt + (B_EW - 1) * 8);
}
template <bool ACT> DI void g2_stream(const unsigned char* src, uint32_t step, uint32_t n, uint32_t d0, int lane) {
  uint32_t dst = d0, fb = BAR + B_FL * 8;
  mbar_wait(BAR + (B_EW + 39) * 8);
  if (ACT) { mbar_wait(BAR + F_ACT * 8); mbar_wait(BAR + (F_ACT + 1) * 8); }
#pragma unroll
  for (int i = 0; i < G2F; i++) {
    const int e = 40 + (13 * i + 12) / 8;
    if (i == 0 || e > G2GATE) mbar_wait(BAR + (B_EW + (e < G2GATE ? G2GATE : (e > 49 ? 49 : e))) * 8);
    if (ACT) CT2B(12 + i);
    bulk_g2s_elect(dst, src, n, fb); src += step; dst += 26624; fb += 8;
  }
  mbar_wait(BAR + (B_EW + 49) * 8);
#pragma unroll 1
  for (int i = G2F; i < 27; i++) {
    if (dst == d0 + G2N * 26624) dst = d0;
    mbar_wait(BAR + (ACT ? F_ACT + ((i * 13 - 26) >> 6) : F_W2 + (i >= W2SPLIT)) * 8);
    mbar_wait(fb + (B_EW - G2F) * 8);
    if (ACT && i < 17) CT2B(12 + i);
    bulk_g2s_elect(dst, src, n, fb); src += step; dst += 26624; fb += 8;
  }
}
DI uint32_t geglu2(float g0, float u0, float g1, float u1, uint32_t sr, uint32_t sm, const uint4& v, const float4& u, uint32_t& prev, uint32_t zero) {
  const float r = __uint_as_float(sr), n = __uint_as_float(sm | (prev & zero));
  const float ga = fmaf(r, g0, fmaf(n, u.x, __uint_as_float(v.x))), gb = fmaf(r, g1, fmaf(n, u.y, __uint_as_float(v.y)));
  const float ua = fmaf(r, u0, fmaf(n, u.z, __uint_as_float(v.z))), ub = fmaf(r, u1, fmaf(n, u.w, __uint_as_float(v.w)));
  const float za = ga * fmaf(ga * ga, 0.0356774081f, 0.7978845608f), zb = gb * fmaf(gb * gb, 0.0356774081f, 0.7978845608f);
  const float pa = ga * ua, pb = gb * ub;
  prev = pack_bf16(fmaf(pa, tanh_fast(za), pa), fmaf(pb, tanh_fast(zb), pb));
  return prev;
}
DI void geglu_store(const float (&a0)[48], const float (&a1)[48], int task, int m, int j, int w, int lane, const Params& P) {
  const uint32_t zero = P.zero;
  uint32_t r = 0, r2 = 0, sr[4], sm[4];
  const uint32_t st = SB + SM_ST + (w * 16 + (lane >> 2)) * 8;
  lds64(sr[0], sm[0], st); lds64(sr[1], sm[1], st + 64); lds64(sr[2], sm[2], st + 512); lds64(sr[3], sm[3], st + 576);
  unsigned char* dst = P.s->actimg + ((m * 216 + tcol(task) + (task < 2 ? 6 : 5) * j) * 2048 + w * 256 + lane * 4);
  const uint32_t uv = SB + SM_UV + 8 * tcol(task) + (lane & 3) * 16, so = SB + SM_STG + (lane >> 4) * 1024 + w * 256 + (lane & 15) * 16;
  uint4 cn = lds128(uv);
#pragma unroll
  for (int i = 0; i < 6; i++) {
    if (i == 5 && task >= 2) break;
    const uint4 cg = cn; const float4 cu = make_float4(bf_lo(cg.x), bf_lo(cg.y), bf_lo(cg.z), bf_lo(cg.w));
    if (i < 5) cn = lds128(uv + 64 * i + 64);
    const uint32_t o0 = geglu2(a0[8 * i], a0[8 * i + 4], a0[8 * i + 1], a0[8 * i + 5], sr[0], sm[0], cg, cu, r, zero);
    const uint32_t o1 = geglu2(a0[8 * i + 2], a0[8 * i + 6], a0[8 * i + 3], a0[8 * i + 7], sr[1], sm[1], cg, cu, r2, zero);
    const uint32_t o2 = geglu2(a1[8 * i], a1[8 * i + 4], a1[8 * i + 1], a1[8 * i + 5], sr[2], sm[2], cg, cu, r, zero);
    const uint32_t o3 = geglu2(a1[8 * i + 2], a1[8 * i + 6], a1[8 * i + 3], a1[8 * i + 7], sr[3], sm[3], cg, cu, r2, zero);
    asm volatile("{.reg .pred p; setp.eq.s32 p, %6, 4;\n@p stmatrix.sync.aligned.m8n8.x4.shared.b16 [%0], {%2,%3,%4,%5};\n"
                 "@!p st.global.u32 [%1], %2; @!p st.global.u32 [%1 + 128], %3; @!p st.global.u32 [%1 + 1024], %4; @!p st.global.u32 [%1 + 1152], %5;}"
                 ::"r"(so + i * 2048), "l"(dst + i * 2048), "r"(o0), "r"(o1), "r"(o2), "r"(o3), "r"(task) : "memory");
    if (i < 4) mbar_arrive_elect(BAR + (task == 4 ? B_EB + i : B_DUMMY) * 8);
  }
  bar_arrive(6 + (task & 1), 160);
}

__global__ void __cluster_dims__(2, 1, 1) __launch_bounds__(768, 1) fused_kernel(const __grid_constant__ Params P, const __grid_constant__ Maps M) {
  extern __shared__ __align__(1024) unsigned char smem[];
  const int kc_ = blockIdx.x >> 1;
  const int lc_ = kc_ < 4 ? (kc_ < 2 ? 64 + kc_ : 58 + kc_) : (kc_ < 36 ? ((kc_ - 4) & 7) * 8 - ((kc_ & 7) == 4 ? 0 : 4) + ((kc_ - 4) >> 3) : (kc_ < 64 ? ((kc_ - 36) % 7) * 8 + 8 + (kc_ - 36) / 7 : kc_ - 2));
  const int cta = 2 * lc_ + (blockIdx.x & 1), c0 = 5 * cta;
  const int m = cta >> 3, j = cta & 7;
  const int fid = 8 * m + j;
  const int warp0 = __shfl_sync(~0u, threadIdx.x >> 5, 0), wg = warp0 >> 2;
  const uint32_t nar = (c0 & 31) > 27;
  const int cs = nar ? (c0 & ~7) : (c0 & ~31), rot = c0 >> 5;
  const int un = (cta & 7) * 16 + (cta >> 3), rq = un & 3, cg = min(un >> 2, 29);
  if (cta >= 128) {
    const int p = cta - 128, tid = threadIdx.x;
    const uint32_t cv = __ldg((const uint32_t*)(P.c + 160 * p) + min(tid, 79)), epoch = ld_relaxed(P.s->epoch + (tid & P.zero)) + 1;
    if (warp0 < 6) { mbar_init10(BAR + 80 * warp0, 1 + P.zero); mbar_expect_if((tid & 31) < 10, BAR + 80 * warp0 + (tid & 31) * 8, 20480); }
    if (warp0 == 0) {
#pragma unroll 1
      for (int i = 0; i < 5; i++) tma2d_elect(SB + i * 20480, &M.wm, 64 * (40 + i), 160 * p, BAR + i * 8);
    }
    if (tid < 480) asm volatile("st.relaxed.gpu.global.v4.u32 [%0], {%1,%1,%1,%1};" ::"l"(P.s->modw + p * (6 * D) + 3 * D + 4 * tid), "r"(epoch - 1) : "memory");
    sts32(SB + SM_SIL + min(tid, 79) * 4, pack_bf16(bf_lo(cv) * rcp(1.f + ex2(bf_lo(cv) * -1.4426950409f)), bf_hi(cv) * rcp(1.f + ex2(bf_hi(cv) * -1.4426950409f))));
    sts128(SB + SM_CH + 224, 1, 0, 0, 0);
    proxy_fence_smem();
    __syncthreads();
    if (wg == 0) {
      uint32_t sl = 0;
#pragma unroll 1
      for (int i = 0; i < 30; i++) {
        float acc[4];
        mbar_wait(BAR + i * 8);
        unit_gemv<16>(acc, dlo(0, 0) + sl * 1280, SM_SIL);
        unsigned* dst = P.s->modw + p * (6 * D) + 64 * (i < 10 ? 40 + i : (i < 20 ? 20 + i : 30 + i)) + 16 * warp0 + ((tid & 31) >> 2);
        if ((tid & 3) == 0) { st_relaxed(dst, (__float_as_uint(acc[0]) & ~63u) | (epoch & 63u)); st_relaxed(dst + 8, (__float_as_uint(acc[2]) & ~63u) | (epoch & 63u)); }
        bar_sync(1, 128);
        if (warp0 == 0 && i < 25) tma2d_elect(SB + sl * 20480, &M.wm, 64 * (i < 5 ? 45 + i : (i < 15 ? 25 + i : 35 + i)), 160 * p, BAR + (i + 5) * 8);
        if (++sl == 5) sl = 0;
      }
    } else {
      const int wv = warp0 - 4; uint32_t sl = 1;
#pragma unroll 1
      for (int i = -2; i < 27; i++) {
        if (wv == 0 && i + 2 < 27) bulk_g2s_elect(SB + (5 + (sl ? sl - 1 : 2)) * 20480, P.wd + (size_t)(64 * (i + 2) + 16 * p) * D, 20480, BAR + (32 + i) * 8);
        if (i >= 0) {
          mbar_wait(BAR + (30 + i) * 8);
#pragma unroll
          for (int h = 0; h < 2; h++) {
            const int n8 = (wv >> 1) * 8 + ((tid + (tid >> 3 & 3) + 4 * h) & 7), jj = n8 / 10;
            const uint4 v = lds128(SB + (5 + sl) * 20480 + ((wv & 1) * 8 + (tid & 7)) * 1280 + n8 * 16);
            sts128(SB + (8 + sl) * 20480 + jj * 1280 + (wv & 1) * 1280 + n8 * 128 + (tid & 7) * 16, v.x, v.y, v.z, v.w);
          }
          proxy_fence_smem();
        }
        if (tid == 704) asm volatile("cp.async.bulk.wait_group.read 1;" ::: "memory");
        bar_sync(2, 640);
        if (tid == 704 && i >= 0) {
#pragma unroll 1
          for (int jj = 0; jj < 8; jj++) bulk_s2g(P.s->w2img + (i * 8 + jj) * 10240 + p * 2560, SB + (8 + sl) * 20480 + jj * 2560, 2560);
          asm volatile("cp.async.bulk.commit_group;" ::: "memory");
          if (i == W2SPLIT - 1) publish_bulk(P.s->cnt + C_W2);
        }
        if (++sl == 3) sl = 0;
      }
      if (tid == 704) { publish_bulk(P.s->cnt + C_W2 + 32); asm volatile("cp.async.bulk.wait_group 0;" ::: "memory"); }
    }
    return;
  }
  uint32_t cv = 0, ep0 = 0;
  if (wg == 5) { cv = __ldg((const uint32_t*)(P.c + 160 * rq) + min(threadIdx.x & 127, 79)); ep0 = ld_relaxed(P.s->epoch + (threadIdx.x & P.zero)); }
  if (warp0 == 23) {
    const int lane = threadIdx.x & 31;
    asm volatile("prefetch.tensormap [%0];" ::"l"(&M.x[nar]) : "memory");
#pragma unroll 1
    for (int i = 0; i < 2; i++) mbar_init10(BAR + B_BOX * 8 + 80 * i, 1 + P.zero);
    mbar_expect_if(lane < 15, BAR + (B_BOX + lane) * 8, lane < 8 ? 16384 >> nar : (lane == 9 ? 4608 : 20480));
    bar_arrive(10, 768);
    bar_sync(8, 672);
    bulk_g2s_elect(SB + SM_GT, P.gtab, 4608, BAR + B_GT * 8);
    bulk_g2s_elect(SB + SM_ROWS, P.x + (size_t)16 * cta * D, 20480, BAR + B_ROWS * 8);
#pragma unroll 1
    for (int i = 0; i < 8; i++) {
      tma2d_elect(SB + i * 16384, &M.x[nar], cs, ((i + rot) & 7) * 256, BAR + (B_BOX + i) * 8);
      if (i == WMPOS) tma2d_elect(SB + SM_WM, &M.wm, 64 * cg, 160 * rq, BAR + B_WM * 8);
    }
    CT(29);
  }
  if (wg == 5) {
#define AUX_IDS(v) const int t = (threadIdx.x & 127) + ((v) & P.zero), lane = t & 31, g = lane >> 2, q = lane & 3; (void)g; (void)q;
    const int w = warp0 & 3;
    const int mat = (un >> 2) & 1;
    unsigned* md1 = P.s->modw + rq * (6 * D) + 64 * cg;
#define MOD_UNIT(bar, dst, on) { float acc[4]; mbar_wait(BAR + (bar) * 8); unit_gemv<16>(acc, dlo(SM_WM, 0), SM_SIL); \
      if (q == 0 && (on)) { st_relaxed(dst + 16 * w + g, (__float_as_uint(acc[0]) & ~63u) | (epoch & 63u)); st_relaxed(dst + 16 * w + 8 + g, (__float_as_uint(acc[2]) & ~63u) | (epoch & 63u)); } }
    {
    AUX_IDS(1)
    const uint32_t epoch = ep0 + 1;

    if (w < 3) {
      mbar_init10(BAR + (w == 0 ? B_PE : 230) * 8, w == 0 ? 8 : 1);
      if (t < 64 && un < 120) st_relaxed(md1 + t, epoch - 1);
      sts32(SB + SM_SIL + min(t, 79) * 4, pack_bf16(bf_lo(cv) * rcp(1.f + ex2(bf_lo(cv) * -1.4426950409f)), bf_hi(cv) * rcp(1.f + ex2(bf_hi(cv) * -1.4426950409f))));
      sts64(SB + SM_CH + 248, epoch, 0); sts128(SB + SM_CH + 224, 1, 0, 0, 0);
      proxy_fence_smem();
      bar_sync(10, 768);
      mbar_expect_if(t < 77, BAR + (B_FW + t) * 8, t < 50 ? (t < 20 ? 12288 : 10240) + (t < 10 ? 16384 : 0) : 26624);
      if (lane < 18) mbar_arrive(BAR + (B_FLG + lane) * 8);
      if (w == 2) { mbar_wait(BAR + B_GT * 8); for (int i = 1; i < 6; i++) bar_arrive(i, 160); }
    }
    {
      {
        uint32_t ra = SB + SM_ROWS + (lane & 15) * 1280 + (w >> 1) * 640 + (((4 * (w & 1) + (lane >> 4)) ^ (lane & 7)) << 4);
        float s1[4] = {}, ga[4] = {}, gb[4] = {};
        CT0(123); mbar_wait(BAR + B_ROWS * 8); CT0(124);
        {
          uint32_t a[10][4]; float s2[4] = {}, gc[4] = {}, gd[4] = {};
#pragma unroll
          for (int s = 0; s < 10; s++) ldsm4(a[s], (ra ^ ((s & 1) * 32)) + (s >> 1) * 128);
#pragma unroll
          for (int s = 0; s < 10; s += 2) {
            mma_bf16(s1, a[s][0], a[s][1], a[s][2], a[s][3], 0x3f803f80u, 0x3f803f80u); mma_bf16(ga, a[s][0], a[s][1], a[s][2], a[s][3], a[s][0], a[s][2]); mma_bf16(gb, a[s][0], a[s][1], a[s][2], a[s][3], a[s][1], a[s][3]);
            const int u = s + 1;
            mma_bf16(s2, a[u][0], a[u][1], a[u][2], a[u][3], 0x3f803f80u, 0x3f803f80u); mma_bf16(gc, a[u][0], a[u][1], a[u][2], a[u][3], a[u][0], a[u][2]); mma_bf16(gd, a[u][0], a[u][1], a[u][2], a[u][3], a[u][1], a[u][3]);
          }
          s1[0] += s2[0]; s1[2] += s2[2]; ga[0] += gc[0]; ga[1] += gc[1]; gb[2] += gd[2]; gb[3] += gd[3];
        }
        if (q == (g >> 1)) { sts64(SB + SM_ROW + w * 128 + g * 8, __float_as_uint(s1[0]), __float_as_uint((g & 1) ? ga[1] : ga[0]));
                             sts64(SB + SM_ROW + w * 128 + 64 + g * 8, __float_as_uint(s1[2]), __float_as_uint((g & 1) ? gb[3] : gb[2])); }
        bar_sync(11, 128);
        const uint32_t pa = SB + SM_ROW + (t & 1) * 64 + ((t >> 1) & 3) * 16;
        const uint4 p0 = lds128(pa), p1 = lds128(pa + 128), p2 = lds128(pa + 256), p3 = lds128(pa + 384);
#define S4(f) ((__uint_as_float(p0.f) + __uint_as_float(p1.f)) + (__uint_as_float(p2.f) + __uint_as_float(p3.f)))
        const float m0 = S4(x) * (1.f / D), m1 = S4(z) * (1.f / D);
        const uint32_t r0 = (__float_as_uint(rsq(fmaxf(fmaf(S4(y), 1.f / D, -m0 * m0), 0.f) + 1e-5f)) & ~63u) | (epoch & 63u);
        const uint32_t r1 = (__float_as_uint(rsq(fmaxf(fmaf(S4(w), 1.f / D, -m1 * m1), 0.f) + 1e-5f)) & ~63u) | (epoch & 63u);
        asm volatile("st.relaxed.gpu.global.v4.u32 [%0], {%1,%2,%3,%4};" ::"l"(P.s->st1 + (t >> 1) * 256 + 2 * cta + (t & 1)),
                     "r"(r0), "f"(-m0 * __uint_as_float(r0)), "r"(r1), "f"(-m1 * __uint_as_float(r1)) : "memory");
        CT0(6);
      }
      MOD_UNIT(B_WM, md1, un < 120)
      CT0(49);
      if (w == 2) { mbar_wait(BAR + (un < 48 ? AGATE : (un < 96 ? LGATE : BGATE)) * 8); tma2d_elect(SB + SM_ROWS, &M.w[mat], 64 * (un >> 3), 160 * rq, BAR + (B_WM + 2) * 8); }
    }
    if (smem_u32(smem) != rk(SB)) __trap();
    if (t < 32) st_relaxed((unsigned*)(P.s->st2 + 8 * fid) + t, epoch - 1);
    }
    {
      const uint32_t epoch = lds32(SB + SM_CH + 248);
      const float hf = mat ? 0.5f : 1.f;
      uint32_t gg[5];
#pragma unroll 1
      for (int rd = 0; rd < (un < 88 ? 2 : 1); rd++) {
        AUX_IDS(epoch + rd)
        const uint32_t uo = (lane >> 3) * 2560 + 5 * w * 128 + (lane & 7) * 16;
        const int fg = 16 * rd + (un >> 3);
        unsigned char* gu = P.s->w1img + ((mat * 4 + rq) * 27 + fg) * 20480;
        unsigned* cnt = P.s->cnt + C_W1 + 32 * (fg < 12 ? fg / 6 : (fg - 2) / 5);
        uint4 v[10];
        mbar_wait(BAR + (B_WM + 2 + rd) * 8);
#pragma unroll
        for (int i = 0; i < 10; i++) {
          const int r8 = 5 * w + (i >> 1), dl = 40 * (r8 & 3) + 5 * (lane & 7) + (r8 >> 2);
          v[i] = lds128(SB + SM_ROWS + rd * 20480 + dl * 128 + ((((lane >> 3) + 4 * (i & 1)) ^ (dl & 7)) << 4));
        }
        if (rd == 0) {
          if (t < 80) { float mv[2]; poll_mod2(mv, P.s->modw + 4 * D + 160 * rq + 2 * t, epoch); sts32(SB + SM_GK + (t >> 2) * 32 + q * 4, pack_bf16(bfr(1.f + mv[0]) * hf, bfr(1.f + mv[1]) * hf)); }
          bar_sync(11, 128);
          CT0(45);
#pragma unroll
          for (int i = 0; i < 5; i++) { const int r8 = 5 * w + i, dl = 40 * (r8 & 3) + 5 * (lane & 7) + (r8 >> 2); gg[i] = lds16(SB + SM_GK + (dl >> 3) * 32 + (dl & 7) * 2) * 0x10001u; }
          {
#pragma unroll
            for (int i = 0; i < 10; i++) sts128(SB + SM_WM + uo + (i & 1) * 10240 + (i >> 1) * 128, bmul(v[i].x, gg[i >> 1]), bmul(v[i].y, gg[i >> 1]), bmul(v[i].z, gg[i >> 1]), bmul(v[i].w, gg[i >> 1]));
            bar_sync(11, 128);
            CT0(55);
            if (w == 3) {
              if (lane == 0) { proxy_fence_smem(); bulk_s2g(gu, SB + SM_WM, 20480); publish_bulk<NREP>(cnt); }
              __syncwarp();
              CT(46);
              if (un < 88) tma2d_elect(SB + SM_WM, &M.w[mat], 64 * (16 + (un >> 3)), 160 * rq, BAR + (B_WM + 3) * 8);
            }
          }
          if (t < 80) { float mv[2]; poll_mod2(mv, P.s->modw + 3 * D + 160 * rq + 2 * t, epoch); sts32(SB + SM_GK + (t >> 2) * 32 + 16 + q * 4, pack_bf16(mv[0] * hf, mv[1] * hf)); proxy_fence_smem(); }
          bar_sync(11, 128);
        }
        {
          float acc[4];
          unit_gemv<32>(acc, dlo(SM_ROWS, 0) + rd * 1280, SM_GK);
          if (q == 0) {
            float* guv = P.s->uv + ((rq * 2 + mat) * F + 64 * fg + 16 * w + g) * 2;
            st_relaxed2(guv, (__float_as_uint(acc[0]) & ~63u) | (epoch & 63u), acc[1]); st_relaxed2(guv + 16, (__float_as_uint(acc[2]) & ~63u) | (epoch & 63u), acc[3]);
          }
        }
        bar_sync(11, 128 + (v[9].x & P.zero));
        if (t == 0) { mbar_arrive(BAR + (B_WF + rd) * 8); if (un >= 88) mbar_arrive(BAR + (B_WF + 1) * 8); }
        CT0(56);
        if (rd) {
          if (fg > 16) mbar_wait(BAR + (LATEG) * 8);
#pragma unroll
          for (int i = 0; i < 10; i++) {
            *(uint4*)(gu + uo + (i & 1) * 10240 + (i >> 1) * 128) = make_uint4(bmul(v[i].x, gg[i >> 1]), bmul(v[i].y, gg[i >> 1]), bmul(v[i].z, gg[i >> 1]), bmul(v[i].w, gg[i >> 1]));
            __nanosleep(WGAP);
          }
          bar_sync(11, 128);
          if (t >= 96 && t < 96 + NREP) publish(cnt + (t - 96) * C_REP);
          __syncwarp();
          if (w == 3) CT(47);
        }
      }
      bar_sync(11, 128);
    }
    reg_dec<40>();
    {
      const uint32_t epoch = lds32(SB + SM_CH + 248);
      AUX_IDS(epoch + 1)
      if (t < 40) { float mv[2]; poll_mod2(mv, P.s->modw + 5 * D + 80 * j + 2 * t, epoch); sts32(SB + SM_GB + t * 4, pack_bf16(mv[0], mv[1])); }
      bar_sync(11, 128);
      if (t == 0) mbar_arrive(BAR + B_GB * 8);
    }
    return;
  }
  {
  const int tid = threadIdx.x + P.zero;
  const int lane = tid & 31, g = lane >> 2, q = lane & 3;
  const int warp = __shfl_sync(~0u, tid >> 5, 0), w = warp & 3, t = tid & 127;
  if (tid == 0) CT(0);

  const int d = c0 + wg;
  const float p_lar = ldbf(P.lar + c0 * 128 + tid), p_aim = ldbf(P.aim + c0 * 128 + tid), p_cr = ldbf(P.cre + c0 * 128 + tid), p_ci = ldbf(P.cim + c0 * 128 + tid);
  const float p_ldt = ldbf(P.ldt + d), p_dsk = ldbf(P.dsk + d);
  bar_arrive(8, 672);
  mbar_init10(BAR + warp * 80, warp < 8 ? 1 : (warp >= 15 && warp < 18 ? 8 : 4));
  bar_arrive(10, 768);
  if (tid == 0) CT(26);

  const uint32_t kb = blk(wg) + w * 2048, mb = kb + 1024;
  const float dt = bfr(expf(p_ldt));
  const float a2 = -bfr(expf(p_lar)) * dt * 1.4426950409f, br = p_aim * dt * 0.1591549431f;
  const float cmax = __uint_as_float(__reduce_max_sync(~0u, __float_as_uint(fabsf(p_cr) + fabsf(p_ci)))), sw_ = pow2_inv(cmax);
  if (lane == 0) stsf(SB + SM_RED + wg * 32 + w * 4, cmax);
  { const int k0 = __reduce_add_sync(~0u, __float2int_rn(p_cr * sw_ * 16777216.f)); if (lane == 0) stsf(SB + SM_RED + wg * 32 + 16 + w * 4, (float)k0 * (1.f / 536870912.f)); }
  const cf z256 = cpow(a2, br, 256.f);
  {
    const cf z64 = cpow(a2, br, 64.f), z1024 = csq(csq(z256)), z8 = cpow(a2, br, 8.f);
    const uint32_t h64 = pack_f16(z64.x, z64.y), h1k = pack_f16(z1024.x, -z1024.y), o = __shfl_xor_sync(~0u, (lane & 1) ? h64 : h1k, 1);
    const uint32_t lo = (lane & 1) ? o : h64, hi = (lane & 1) ? h1k : o;
    sts64(mb + lane * 8, __byte_perm(lo, hi, 0x5410), __byte_perm(lo, hi, 0x7632));
    cf b[8]; b[0] = {0.0625f, 0.f}; b[1] = {0.0625f * z8.x, 0.0625f * z8.y};
#pragma unroll
    for (int k = 2; k < 8; k++) b[k] = cmul(b[k - 1], z8);
    sts128(kb + lane * 16, pack_f16(b[0].x, b[1].x), pack_f16(b[2].x, b[3].x), pack_f16(b[4].x, b[5].x), pack_f16(b[6].x, b[7].x));
    sts128(kb + 512 + lane * 16, pack_f16(b[0].y, b[1].y), pack_f16(b[2].y, b[3].y), pack_f16(b[4].y, b[5].y), pack_f16(b[6].y, b[7].y));
  }
  __syncwarp();
  const uint32_t fo = ((lane >> 3) & 1) * 512 + ((lane >> 4) * 8 + (lane & 7)) * 16;
  uint32_t v0[2][4]; uint4 em[4];
  ldsm4t(v0[0], kb + fo); ldsm4t(v0[1], kb + 256 + fo);
#pragma unroll
  for (int i = 0; i < 4; i++) em[i] = lds128(mb + (4 * i + q) * 16);
  __syncwarp();
  CT0(1 + wg);
  {
    const cf zc = cpow(a2, -br, 1.f);
    cf u[9]; u[0] = {p_cr * (0.5f * sw_), p_ci * (-0.5f * sw_)};
#pragma unroll
    for (int k = 1; k < 9; k++) u[k] = cmul(u[k - 1], zc);
    const uint32_t h256 = pack_f16(z256.x, -z256.y); const __half2 er = __low2half2(H2(h256)), ei = __high2half2(H2(h256));
    uint32_t r[4], n[4];
    r[1] = pack_f16(u[2].x, u[6].x); n[1] = pack_f16(u[2].y, u[6].y); hcmul(r[0], n[0], r[1], n[1], er, ei);
    sts128(kb + 1024 + lane * 16, r[0], r[1], pack_f16(u[1].x, u[3].x), pack_f16(u[5].x, u[7].x));
    sts128(kb + 1536 + lane * 16, n[0], n[1], pack_f16(u[1].y, u[3].y), pack_f16(u[5].y, u[7].y));
    r[0] = pack_f16(u[8].x, u[4].x); n[0] = pack_f16(u[8].y, u[4].y);
#pragma unroll
    for (int k = 1; k < 4; k++) hcmul(r[k], n[k], r[k - 1], n[k - 1], er, ei);
    sts128(kb + lane * 16, r[0], r[1], r[2], r[3]); sts128(kb + 512 + lane * 16, n[0], n[1], n[2], n[3]);
  }
  __syncwarp();
  {
    uint32_t ua[2][4], ub[2][4], kacc[2][3][2] = {};
    ldsm4t(ua[0], kb + fo); ldsm4t(ub[0], kb + 1024 + fo); ldsm4t(ua[1], kb + 256 + fo); ldsm4t(ub[1], kb + 1280 + fo);
#pragma unroll
    for (int mm = 0; mm < 4; mm++) {
      const uint4 e = em[mm]; const int s = mm >> 1, o = 2 * (mm & 1);
      uint32_t a0[4], a1[4], cr, ci;
      a0[0] = v0[s][o]; a0[2] = v0[s][o + 1];
      hcmul(a0[1], a0[3], a0[0], a0[2], H2(e.x), H2(e.y));
      hcmul(a1[0], a1[2], a0[1], a0[3], H2(e.x), H2(e.y));
      hcmul(a1[1], a1[3], a1[0], a1[2], H2(e.x), H2(e.y));
      hcmul(cr, ci, ua[s][o], ua[s][o + 1], H2(e.z), H2(e.w));
      mma_f16(kacc[0][0], a0, ua[s][o], ua[s][o + 1]); mma_f16(kacc[0][1], a0, ub[s][o], ub[s][o + 1]); mma_f16(kacc[0][2], a0, cr, ci);
      mma_f16(kacc[1][0], a1, ua[s][o], ua[s][o + 1]); mma_f16(kacc[1][1], a1, ub[s][o], ub[s][o + 1]); mma_f16(kacc[1][2], a1, cr, ci);
    }
    __syncwarp();
#pragma unroll
    for (int nt = 0; nt < 3; nt++)
      stsm4t(kb + nt * 512 + lane * 16, kacc[0][nt][0], kacc[0][nt][1], kacc[1][nt][0], kacc[1][nt][1]);
  }
  bar_sync(1 + wg, 160);
  BOXP(21);
  CT0(7 + wg);
  uint2 go[5];
  if (w < 3) {
    const uint32_t a = blk(wg) + t * 16;
    const uint4 cm = lds128(SB + SM_RED + wg * 32), p0 = lds128(a), p1 = lds128(a + 2048), p2 = lds128(a + 4096), p3 = lds128(a + 6144);
    const float dd = p_dsk * rcp(2.f * dt);
    const float su = pow2_inv(fmaf((__uint_as_float(cm.x) + __uint_as_float(cm.y)) + (__uint_as_float(cm.z) + __uint_as_float(cm.w)), 32.f, fabsf(dd)));
    const float f0 = su * 64.f * __uint_as_float(cm.x & 0x7f800000u), f1 = su * 64.f * __uint_as_float(cm.y & 0x7f800000u), f2 = su * 64.f * __uint_as_float(cm.z & 0x7f800000u), f3 = su * 64.f * __uint_as_float(cm.w & 0x7f800000u);
    const __half2 h01 = H2(pack_f16(f0, f1)), h23 = H2(pack_f16(f2, f3));
#define KSUM(f) U(__hfma2(H2(p0.f), __low2half2(h01), __hfma2(H2(p1.f), __high2half2(h01), __hfma2(H2(p2.f), __low2half2(h23), __hmul2(H2(p3.f), __high2half2(h23))))))
    sts128(blk(wg) + KV + (8 * w + (lane & 7)) * 80 + (lane >> 3) * 16, KSUM(x), KSUM(y), KSUM(z), KSUM(w));
    if (t == 64) {
      const uint4 c = lds128(SB + SM_RED + wg * 32 + 16);
      sts32(blk(wg) + KV + 64, pack_f16(fmaf(dd, su, fmaf(__uint_as_float(c.x), f0, __uint_as_float(c.y) * f1) + fmaf(__uint_as_float(c.z), f2, __uint_as_float(c.w) * f3)), 0.f));
      stsf(SB + SM_CH + wg * 32 + 24, 2.f * dt * rcp(su));
    }
  }
#pragma unroll
  for (int k = 0; k < 5; k++) if (k < 4 || w < 2) lds64(go[k].x, go[k].y, SB + SM_GT + (128 * k + t) * 8);
  bar_sync(1 + wg, 128);
  BOXP(22);
#pragma unroll
  for (int k = 0; k < 5; k++) if (k < 4 || w < 2) {
    const uint32_t kv = blk(wg) + KV;
    sts64(blk(wg) + (128 * k + t) * 8, __byte_perm(lds16(kv + (go[k].x & 0xffffu)), lds16(kv + (go[k].x >> 16)), 0x5410), __byte_perm(lds16(kv + (go[k].y & 0xffffu)), lds16(kv + (go[k].y >> 16)), 0x5410));
  }
  if (t == 127) sts64(SB + SM_CH + wg * 32, lds16(blk(wg) + KV + KV_512) * 0x10001u, (lds16(blk(wg) + KV + KV_1024) * 0x10001u) ^ 0x80008000u);
  CT0(12 + wg);
  BOXP(23);
  bar_sync(9, 640);
  if (tid == 0) CT(17);
  }

  if (wg == 4) {
    reg_dec<56>();
    {
    ROLE_IDS
    if (w == 3) {
      if (lane < 5) {
        float mv[3]; poll_mod<3>(mv, P.s->modw + c0 + lane, D, epoch);
        const float ca1 = bfr(1.f + mv[1]), hs = pow2_inv(fmaf(fabsf(mv[0]), 0.04f, fabsf(ca1)));
        sts64(SB + SM_CH + lane * 32 + 16, pack_f16(ca1 * hs, ca1 * hs), pack_f16(mv[0] * hs, mv[0] * hs));
        stsf(SB + SM_CH + lane * 32 + 8, mv[2] * ldsf(SB + SM_CH + lane * 32 + 24) * rcp(hs));
      }
      __syncwarp(); mbar_arrive_elect(BAR + B_AB * 8); CT(28);
    }
#pragma unroll 1
    for (int k = w == 3; k < 2; k++) { mbar_wait(BAR + (B_HS + k) * 8); box_sums(k ? 11 + w : w, lane); }
    CT0(25);
    bar_sync(5, 128);
    }
    reg_dec<40>();
    ROLE_IDS
    if (w == 0) {
      mbar_wait(BAR + (B_PD + 1) * 8);
      uint32_t dst = SB + SM_W;
#pragma unroll 1
      for (uint32_t tk = 0; tk < 5; tk++) {
        const uint32_t n = tk < 2 ? 12288 : 10240;
        mbar_wait(BAR + (F_W1 + tk) * 8);
#pragma unroll 1
        for (uint32_t i = tk * 10; i < tk * 10 + 10; i++) {
          if (i >= 1) mbar_wait(BAR + (i < 5 ? B_WF + (i >= 3) : B_EW + i - (i < 25 ? 5 : 6)) * 8);
          const uint32_t kc = i - tk * 10;
          tma5d_elect(dst, &M.w1[tk >= 2], 0, tcol(tk) + (n >> 11) * j, 2 * (kc & 1), kc >> 1, BAR + (B_FW + i) * 8);
          dst += n; if (dst == SB + SM_W + 61440) dst = SB + SM_W;
        }
      }
      mbar_wait(BAR + F_W2 * 8);
      g2_stream<false>(P.s->w2img + j * 10240, 81920, 10240, SB + 16384, lane);
    } else if (w == 1) {
#pragma unroll 1
      for (uint32_t c = 0; c < 5; c++) {
        mbar_wait(BAR + (B_PE + min(2 * c + 1, 4u)) * 8);
        mbar_wait(BAR + (F_X1 + c) * 8);
        CT(60 + c);
        tma4d_elect(SB + SM_X + c * 32768, &M.x1, 0, 0, 2 * m, c, BAR + (B_FW + 2 * c) * 8);
        tma4d_elect(SB + SM_X + c * 32768 + 16384, &M.x1, 0, 64, 2 * m, c, BAR + (B_FW + 2 * c + 1) * 8);
      }
      if (lane == 0) st_relaxed(P.s->tsync + cta, (epoch - 1) & 31u);
      mbar_wait(BAR + (B_EW + SYNCAT) * 8);
      uint32_t tn = clock(), g0; asm volatile("mov.u32 %0, %globaltimer_lo;" : "=r"(g0));
      g0 = (g0 & ~31u) | (epoch & 31u);
      if (lane == 0) st_relaxed(P.s->tsync + cta, g0);
      {
        int dmax = 0;
#pragma unroll 1
        for (int k = 0; k < (SYNCG + 31) / 32; k++) {
          uint32_t v; int it = 0;
          do v = ld_relaxed(P.s->tsync + (cta & ~(SYNCG - 1)) + ((32 * k + lane) & (SYNCG - 1))); while (((v ^ epoch) & 31u) && ++it < 100000);
          dmax = max(dmax, (int)(v - g0));
        }
        tn += min(__reduce_max_sync(~0u, dmax), 4000) * 7 / 4 + (10 * SYNCT - 1 - SYNCAT) * 320 + SYNCD;
        while ((int)(clock() - tn) < 0) {}
        mbar_arrive_elect(BAR + B_GO * 8);
      }
      g2_stream<true>(P.s->actimg + m * (432 * 1024), 16384, 16384, SB, lane);
      mbar_wait(BAR + (B_EL + 27 - G2N) * 8);
      tma2d_elect(SB + G_RES, &M.res, 128 * m, 80 * j, BAR + B_RES * 8); tma2d_elect(SB + G_RES + 10240, &M.res, 128 * m + 64, 80 * j, BAR + B_RES * 8);
    } else if (w == 2) {
#pragma unroll 1
      for (int c = 0; c < 5; c++) {
        mbar_wait(BAR + (B_PE + c) * 8);
        proxy_fence_smem();
        if (lane == 0) { bulk_s2g(P.s->x1t + (c0 + c) * 4096, blk(c) + XO + c * 16, 4096); publish_bulk<NREP>(P.s->cnt + C_X1 + 32 * c); if (c == 1 || c == 4) mbar_arrive(BAR + (B_PD + (c & 1)) * 8); }
        CT(50 + c);
        __syncwarp();
      }
#pragma unroll 1
      for (int tk = 0; tk < 5; tk++) {
        unsigned char* dst = P.s->actimg + (m * 216 + tcol(4) + 5 * j) * 2048;
        if (tk == 4) {
#pragma unroll 1
          for (int i = 0; i < 4; i++) { mbar_wait(BAR + (B_EB + i) * 8); if (lane == 0) { proxy_fence_smem(); bulk_s2g(dst + i * 2048, SB + SM_STG + i * 2048, 2048); } __syncwarp(); }
        }
        bar_sync(6 + (tk & 1), 160);
        if (lane == 0) {
          if (tk < 4) publish(P.s->cnt + C_ACT + m * 32 + 4 * tk);
          else { proxy_fence_smem(); bulk_s2g(dst + 8192, SB + SM_STG + 8192, 2048); publish_bulk(P.s->cnt + C_ACT + m * 32 + 4 * tk); }
        }
        __syncwarp();
      }
    } else {
      mbar_wait(BAR + (F_X1 + 1) * 8);
#pragma unroll 1
      for (int tk = 0; tk < 10; tk++) {
        const int tw = tk < 4 ? 48 : 40, tc = 8 * tcol(tk >> 1);
        if (2 * lane < tw) {
          const float* p = P.s->uv + ((tk & 1) * F + tc + tw * j + 2 * lane) * 2;
          uint4 p0, p1, p2, p3; int it = 0;
          do { p0 = ld_relaxed4(p); p1 = ld_relaxed4(p + 4 * F); p2 = ld_relaxed4(p + 8 * F); p3 = ld_relaxed4(p + 12 * F); }
          while ((((p0.x ^ epoch) | (p0.z ^ epoch) | (p1.x ^ epoch) | (p1.z ^ epoch) | (p2.x ^ epoch) | (p2.z ^ epoch) | (p3.x ^ epoch) | (p3.z ^ epoch)) & 63u) && ++it < 100000);
          const uint32_t u = pack_bf16(S4(x), S4(z));
          sts64(SB + SM_UV + tc + lane * 16 + (tk & 1) * 8, uv_word(S4(y), u & 0xffffu), uv_word(S4(w), u >> 16));
        }
        __syncwarp();
        if (tk & 1) mbar_arrive_elect(BAR + (B_UV + (tk >> 1)) * 8);
      }
    }
    return;
  } else if (wg >= 2) {
    reg_dec<56>();
    {
    ROLE_IDS
    const int h = wg - 2, tau = 128 * h + t;
    {
      uint4 st[4]; const uint4* src = P.s->st1 + (cta >> 3) * (L / 2) + tau;
#pragma unroll
      for (int k = 0; k < 4; k++) st[k] = ld_relaxed4(src + 256 * k);
      {
        const bool two = (c0 & 7) > 3, hi = g < (c0 & 7);
        const uint32_t o0 = (c0 - cs) >> 3, sw = (lane >> (1 + nar)) & (3 >> nar), gs = 2048 >> nar, slot = (4 * h + w - rot) & 7, xb = SB + slot * 16384;
        uint32_t a0 = xb + ((lane * 64) >> nar) + ((o0 ^ sw) << 4), a1 = xb + ((lane * 64) >> nar) + (((o0 + 1) ^ sw) << 4), cl = ((lane & 7) - c0) & 7,
                 xd = (cl < 5 ? blk(cl) + XO + (4 * h + w) * 512 : xb) + cl * 16 + (lane >> 3) * 16;
        mbar_wait(BAR + (B_BOX + slot) * 8);
#pragma unroll 1
        for (int i = 0; i < 4; i++, a0 += 2 * gs, a1 += 2 * gs, xd += 128) {
          uint32_t r[2][4];
#pragma unroll
          for (int k = 0; k < 2; k++) ldsm4t(r[k], a0 + k * gs);
          if (two) {
#pragma unroll
            for (int k = 0; k < 2; k++) { uint32_t r2[4]; ldsm4t(r2, a1 + k * gs); if (hi) { r[k][0] = r2[0]; r[k][1] = r2[1]; r[k][2] = r2[2]; r[k][3] = r2[3]; } }
          }
#pragma unroll
          for (int k = 0; k < 2; k++) stsm4(xd + k * 64, r[k][0], r[k][1], r[k][2], r[k][3]);
        }
        __syncwarp();
        if (h) CT0(18);
      }
      for (int it = 0; it < 100000; it++) {
        uint32_t bad = 0;
#pragma unroll
        for (int k = 0; k < 4; k++) bad |= (st[k].x ^ epoch) | (st[k].z ^ epoch);
        if (!(bad & 63u)) break;
#pragma unroll
        for (int k = 0; k < 4; k++) st[k] = ld_relaxed4(src + 256 * k);
      }
      if (h) CT0(19);
      mbar_wait(BAR + B_AB * 8);
      bar_sync(12, 256);
      if (h) CT0(20);
      const uint32_t ho = SB + (t & 1) * HO + (tau >> 1) * 16 + 128;
      const uint32_t zo = SB + (t < 64 ? (t < 32 ? A5 : A3 - 512) + t * 16 : (t < 80 ? ((t >> 3) & 1) * HO + (t & 7) * 16 : A9));
#pragma unroll
      for (int c = 0; c < 5; c++) {
        uint32_t ha, hb, o[4]; lds64(ha, hb, SB + SM_CH + c * 32 + 16);
        const uint4 x = lds128(blk(c) + XO + c * 16 + tau * 16);
#pragma unroll
        for (int k = 0; k < 4; k++) o[k] = hfma(pack_f16(fmaf(bf_lo(wsel(x, k)), __uint_as_float(st[k].x), __uint_as_float(st[k].y)), fmaf(bf_hi(wsel(x, k)), __uint_as_float(st[k].z), __uint_as_float(st[k].w))), ha, hb);
        sts128(ho + c * 16384, o[0], o[1], o[2], o[3]);
        if (t < 81 && h == (c & 1)) sts128(zo + c * 16384, 0, 0, 0, 0);
        if (c == 0 || c == 4) { __syncwarp(); mbar_arrive_elect(BAR + (B_HS + (c >> 2)) * 8); }
      }
      if (h) CT0(27);
    }
    mbar_wait(BAR + (B_HS + 1) * 8);
    box_sums(3 + 4 * h + w, lane);
    const uint32_t pb = SB + SM_PART + (t & 1) * PO + (tau >> 1) * 16, xo = blk(0) + XO + tau * 16;
    const uint32_t ho = SB + (t & 1) * HO + (t >> 1) * 16 + 128, hp = SB + ((t + 1) & 1) * HO + ((t + 15) >> 1) * 16, ha = SB + HO + 8 + ((t & 1) || tau < 64 ? 0 : ((tau >> 1) - 25) * 16);
#pragma unroll EPIUNR
    for (int c = 0; c < 5; c++) {
      const uint32_t PBc = (c < 3 ? c : c - 3) * PBUF;
      const uint4 kc = lds128(SB + SM_CH + c * 32), x = lds128(xo - c * 10224);
      uint4 y;
      if (h || w >= 2) {
        uint32_t hv, hw; lds64(hv, hw, ha + c * 16384);
        const uint32_t y0 = hfma(hadd(__byte_perm(hw, 0, 0x3232), hw & 0xffffu), kc.x, 0);
        if (h) {
          const uint4 a = lds128(hp + c * 16384); uint32_t b0, b1; lds64(b0, b1, ho + c * 16384);
          const uint32_t u0 = __byte_perm(a.y, a.z, 0x5432), u1 = __byte_perm(a.z, a.w, 0x5432), u2 = __byte_perm(a.w, b0, 0x5432), u3 = __byte_perm(b0, b1, 0x5432);
          mbar_wait(BAR + (B_PF + c) * 8);
          const uint4 p2 = lds128(pb + PBc + PP2), p3 = lds128(pb + PBc + PP3);
          y.x = hadd(hfma(u0, kc.y, p3.x), p2.x); y.y = hadd(hfma(u1, kc.y, p3.y), p2.y); y.z = hadd(hfma(u2, kc.y, p3.z), p2.z); y.w = hadd(hfma(u3, kc.y, p3.w), p2.w);
        } else {
          mbar_wait(BAR + (B_PF + c) * 8);
          y = lds128(pb + PBc + PP2);
        }
        y.x = hadd(y.x, y0);
      } else { y = make_uint4(0, 0, 0, 0); mbar_wait(BAR + (B_PF + c) * 8); }
      const uint4 p0 = lds128(pb + PBc), p1 = lds128(pb + PBc + PSZ);
      uint32_t o[4];
#pragma unroll
      for (int k = 0; k < 4; k++) {
        const float2 yf = __half22float2(H2(hadd(hadd(wsel(y, k), wsel(p1, k)), wsel(p0, k))));
        o[k] = pack_bf16(fmaf(__uint_as_float(kc.z), yf.x, bf_lo(wsel(x, k))), fmaf(__uint_as_float(kc.z), yf.y, bf_hi(wsel(x, k))));
      }
      sts128(xo - c * 10224, o[0], o[1], o[2], o[3]);
      __syncwarp();
      mbar_arrive_elect(BAR + (B_PE + c) * 8);
      if (h) CT0(40 + c);
    }
    bar_sync(1 + wg, 128);
    }
    if (wg == 3) {
      reg_dec<24>();
      ROLE_IDS
      poll_flags(P, 0x3fb80u, cta, m, fid, lane, w, epoch);
      if (cta == 0 && t == 0) P.s->epoch[0] = epoch;
      return;
    }
    reg_dec<32>();
    ROLE_IDS
    float s0 = 0, s1 = 0, q0 = 0, q1 = 0;
    uint32_t ra = SB + SM_X + (j >> 2) * 8192 + (16 * w + (lane >> 4) * 8 + (lane & 7)) * 128 + (((2 * (j & 3) + ((lane >> 3) & 1)) ^ (lane & 7)) << 4);
#pragma unroll 1
    for (int kc = 0; kc < 10; kc++, ra += 16384) {
      mbar_wait(BAR + (B_FW + kc) * 8);
      uint32_t a[4]; ldsm4t(a, ra);
#pragma unroll
      for (int i = 0; i < 4; i += 2) {
        const float u0 = bf_lo(a[i]), u1 = bf_hi(a[i]), v0 = bf_lo(a[i + 1]), v1 = bf_hi(a[i + 1]);
        s0 += u0 + u1; q0 = fmaf(u0, u0, fmaf(u1, u1, q0)); s1 += v0 + v1; q1 = fmaf(v0, v0, fmaf(v1, v1, q1));
      }
    }
    {
      const float a = ((q & 1) ? s1 : s0) + __shfl_xor_sync(~0u, (q & 1) ? s0 : s1, 1), b = ((q & 1) ? q1 : q0) + __shfl_xor_sync(~0u, (q & 1) ? q0 : q1, 1);
      stsf(SB + SM_ST + w * 128 + (q & 1) * 64 + g * 8 + (q >> 1) * 4, ((q & 2) ? b : a) + __shfl_xor_sync(~0u, (q & 2) ? a : b, 2));
    }
    bar_sync(3, 128);
    if (w == 0) {
      const uint32_t pa = SB + SM_ST + (lane & 7) * 16;
      const uint4 p0 = lds128(pa), p1 = lds128(pa + 128), p2 = lds128(pa + 256), p3 = lds128(pa + 384);
      const float m0 = S4(x) * (1.f / D), m1 = S4(z) * (1.f / D);
      const uint32_t r0 = (__float_as_uint(rsq(fmaxf(fmaf(S4(y), 1.f / D, -m0 * m0), 0.f) + 1e-5f)) & ~63u) | (epoch & 63u);
      const uint32_t r1 = (__float_as_uint(rsq(fmaxf(fmaf(S4(w), 1.f / D, -m1 * m1), 0.f) + 1e-5f)) & ~63u) | (epoch & 63u);
      if (lane < 8) asm volatile("st.relaxed.gpu.global.v4.u32 [%0], {%1,%2,%3,%4};" ::"l"(P.s->st2 + 8 * fid + lane), "r"(r0), "f"(-m0 * __uint_as_float(r0)), "r"(r1), "f"(-m1 * __uint_as_float(r1)) : "memory");
      CT(57);
      uint4 v0, v1; int it = 0;
      do { v0 = ld_relaxed4(P.s->st2 + 64 * m + lane); v1 = ld_relaxed4(P.s->st2 + 64 * m + 32 + lane); } while ((((v0.x ^ epoch) | (v0.z ^ epoch) | (v1.x ^ epoch) | (v1.z ^ epoch)) & 63u) && ++it < 100000);
      sts128(SB + SM_ST + lane * 16, v0.x, v0.y, v0.z, v0.w); sts128(SB + SM_ST + 512 + lane * 16, v1.x, v1.y, v1.z, v1.w);
      __syncwarp();
      mbar_arrive_elect(BAR + B_ST * 8);
      CT(58);
    }
    mbar_wait(BAR + (B_EW + 39) * 8);
    bar_sync(3, 128);
    reg_inc<104>();
  } else {
    if (wg == 0) {
      reg_inc<CONVREG>();
      ROLE_IDS
      const uint32_t fa = (w & 1) * PD1 + (8 * (w >> 1) + g + 144 - 2 * q) * 8, f2 = (8 * w + g + 48 - 4 * q) * 8, f3 = (8 * w + g + 32 - 2 * q) * 8;
      const uint32_t s0 = SB + SM_PART + (w & 1) * PSZ + (w >> 1) * PO + (16 * (w & 1) + lane) * 16, s1 = s0 + ((w & 1) && lane >= 16 ? 1536 - 2048 : 1536);
      const uint32_t s2 = SB + SM_PART + PP2 + (lane & 1) * PO + (32 + 16 * (lane >> 3) + 4 * w + ((lane & 7) >> 1)) * 16;
      const uint32_t s3 = SB + SM_PART + PP3 + ((lane >> 3) & 1) * PO + (64 + 32 * (lane >> 4) + 8 * w + (lane & 7)) * 16;
      uint32_t a[2][9][4], r[12][4], acc[32], c2[12], c3[8], o[16];
#define LOAD_D(c) _Pragma("unroll") for (int k = 0; k < 9; k++) { lds64(a[(c) & 1][k][0], a[(c) & 1][k][1], blk(c) + fa - k * 128); lds64(a[(c) & 1][k][2], a[(c) & 1][k][3], blk(c) + fa - k * 128 - 64); }
#define LOAD_R(c) _Pragma("unroll") for (int k = 0; k < 12; k++) { \
          const uint32_t ad = blk(c) + (k < 8 ? f2 + (k < 4 ? P5 : P3) - (k & 3) * 128 : f3 + (k < 10 ? P7 : P9) - (k & 1) * 128); \
          if (k < 8 && ((k & 3) == 0 || (k & 3) == 3)) { const bool z = (k & 3) ? w < 2 : w >= 2; lds64_if(!z, r[k][0], r[k][1], ad); lds64_if(!z, r[k][2], r[k][3], ad - 8); } \
          else { lds64(r[k][0], r[k][1], ad); lds64(r[k][2], r[k][3], ad - (k < 8 ? 8 : 64)); } }
#define ISSUE_D(c) { wg_fence(); wgmma_h128<0, dhi(128, 0), 0>(acc, a[(c) & 1][0], dlo((c) * 16384, HO)); \
          _Pragma("unroll") for (int k = 1; k < 9; k++) wgmma_h128<0, dhi(128, 0), 1>(acc, a[(c) & 1][k], dlo((c) * 16384, HO) + k); wg_commit(); }
#pragma unroll
      for (int k = 0; k < 8; k++) r[k][0] = r[k][1] = r[k][2] = r[k][3] = 0;
      LOAD_D(0) LOAD_R(0)
      mbar_wait(BAR + B_HS * 8); proxy_fence_smem();
      ISSUE_D(0)
#pragma unroll
      for (int c = 0; c < 5; c++) {
        const uint32_t bo = (c < 3 ? c : c - 3) * PBUF, b = dlo(c * 16384, 128);
        if (c == 0) { mbar_wait(BAR + B_SG * 8); mbar_wait(BAR + (B_HS + 1) * 8); proxy_fence_smem(); }
        if (c & 1) { mbar_wait(BAR + (B_SG + c) * 8); mbar_wait(BAR + (B_SG + c + 1) * 8); proxy_fence_smem(); }
        wg_fence();
        wgmma_h48<1, dhi(512, 0), 0>(c2, r[0], b + A5 / 16);
#pragma unroll
        for (int k = 1; k < 8; k++) wgmma_h48<1, dhi(512, 0), 1>(c2, r[k], b + (k < 4 ? A5 : A3) / 16 + (k & 3) * 16);
        wgmma_h32<1, dhi(512, 0), 0>(c3, r[8], b + A7 / 16);
#pragma unroll
        for (int k = 9; k < 12; k++) wgmma_h32<1, dhi(512, 0), 1>(c3, r[k], b + (k < 10 ? A7 : A9) / 16 + (k & 1) * 16);
        wg_commit();
        if (c < 4) LOAD_D(c + 1)
        if (c >= 3) mbar_wait(BAR + (B_PE + c - 3) * 8);
        wg_wait<1>();
        reg_fence(acc);
        o[0] = acc[0];
#pragma unroll
        for (int G = 1; G < 16; G++) o[G] = hadd(acc[2 * G], acc[2 * G - 1]);
        reg_fence(o);
        if (c < 4) ISSUE_D(c + 1)
        CT0(30 + c);
        if (w & 1) o[14] = o[15] = 0;
        stsm4t(s0 + bo, o[0], o[1], o[2], o[3]); stsm4t(s0 + bo + 512, o[4], o[5], o[6], o[7]); stsm4t(s0 + bo + 1024, o[8], o[9], o[10], o[11]); stsm4t(s1 + bo, o[12], o[13], o[14], o[15]);
        if (c < 4) wg_wait<1>(); else wg_wait<0>();
        reg_fence(c2); reg_fence(c3);
        CT0(35 + c);
        stsm4(s2 + bo, c2[0], hadd(c2[2], c2[1]), hadd(c2[4], c2[3]), hadd(c2[6], c2[5]));
        stsm2(s2 + bo + 1024, hadd(c2[8], c2[7]), hadd(c2[10], c2[9]));
        stsm4(s3 + bo, c3[0], c3[2], hadd(c3[4], c3[1]), hadd(c3[6], c3[3]));
        __syncwarp();
        mbar_arrive_elect(BAR + (B_PF + c) * 8);
        if (c < 4) LOAD_R(c + 1)
      }
      bar_sync(1, 128);
      reg_dec<152>();
    } else {
      reg_dec<24>();
      {
        ROLE_IDS
        mbar_wait(BAR + B_PF * 8);
        poll_flags(P, 0x7fu, cta, m, fid, lane, w, epoch);
      }
      bar_sync(2, 128);
      reg_inc<152>();
    }
    ROLE_IDS
    CT0(90 + wg);
    {
      float a0[48], a1[48];
#pragma unroll 1
      for (int task = wg; task < 5; task += 2) {
        if (task == 0) mbar_wait(BAR + (T0GATE) * 8);
        if (SYNCG && task == SYNCT) mbar_wait(BAR + B_GO * 8);
        if (STRICT && task > SYNCT) mbar_wait(BAR + (B_EW + 10 * task - 1 - STRICT) * 8);
        if (task < 2) gemm1_task<48>(a0, a1, task); else gemm1_task<40>(a0, a1, task);
        CT0(102 + task);
        mbar_wait(BAR + (B_UV + task) * 8);
        mbar_wait(BAR + (task < 4 ? B_ST : B_EW + 49) * 8);
        geglu_store(a0, a1, task, m, j, w, lane, P);
        CT0(107 + task);
      }
    }
    bar_sync(1 + wg, 128);
    if (wg == 0) { reg_dec<24>(); return; }
    reg_dec<104>();
  }
  {
    ROLE_IDS
    {
      float acc[40] = {}; uint32_t gb[3][4], xv[5][4];
      reg_fence(acc);
      uint32_t a = dlo(0, 2048) + (wg - 1) * 64, bx = BAR + B_FL * 8;
      const uint32_t a0 = a, bo = dlo(16384, 1280) - a;
      mbar_wait(BAR + B_GB * 8);
#pragma unroll
      for (int k = 0; k < 3; k++) ldsm4(gb[k], SB + SM_GB + k * 64 + (lane >> 3) * 16);
      CT0(100 - wg);
      if (STRICT) mbar_wait(BAR + (B_EW + 49 - STRICT) * 8);
#pragma unroll 1
      for (int i = 0; i < 27; i++) {
        mbar_wait(bx);
        if (wg == 1 && (i & 3) == 0) CT2(1 + (i >> 2));
        wg_fence();
#pragma unroll
        for (int k = 0; k < 4; k++) wgmma_n80<0, 1, dhi(128, 0), dhi(128, 0)>(acc, a + k * 256, a + bo + k * 160, 1);
        wg_commit();
        a += 1664; if (a == a0 + G2N * 1664) a = a0;
        bx += 8;
        wg_wait<G2U>();
        mbar_arrive_elect(i >= G2U ? bx + (B_EW - 1 - G2U) * 8 : BAR + B_DUMMY * 8);
      }
      mbar_wait(BAR + B_RES * 8);
      mbar_wait(BAR + (B_EL + 28 - G2N) * 8);
#pragma unroll
      for (int k = 0; k < 5; k++) ldsm4t(xv[k], SB + G_RES + (wg - 1) * 10240 + (16 * k + (lane >> 4) * 8 + (lane & 7)) * 128 + (((2 * w + ((lane >> 3) & 1)) ^ (lane & 7)) << 4));
      wg_wait<0>();
      reg_fence(acc);
      CT0(93 + wg);
      const uint32_t so = SB + G_RES + 26624 + ((wg - 1) * 4 + w) * 2560;
#pragma unroll
      for (int k = 0; k < 5; k++) {
        uint32_t o[4];
#pragma unroll
        for (int e = 0; e < 4; e++) { const int n = 2 * k + (e >> 1); const uint32_t gw = gb[n >> 2][n & 3], v = xv[k][e]; o[e] = pack_bf16(fmaf(bf_lo(gw), acc[8 * k + 2 * e], bf_lo(v)), fmaf(bf_hi(gw), acc[8 * k + 2 * e + 1], bf_hi(v))); }
        stsm4(so + (lane & 15) * 160 + k * 32 + (lane >> 4) * 16, o[0], o[1], o[2], o[3]);
      }
      CT2(8);
      proxy_fence_smem();
      __syncwarp();
      CT2(9);
      if (lane == 0) asm volatile("cp.async.bulk.tensor.2d.global.shared::cta.bulk_group [%0, {%2, %1}], [%3];\ncp.async.bulk.commit_group;\ncp.async.bulk.wait_group.read 0;"
                                  ::"l"(&M.out), "r"(128 * m + 64 * (wg - 1) + 16 * w), "r"(80 * j), "r"(so) : "memory");
      if (wg == 1) return;
      CT0(101);
    }
  }
}

extern "C" void kernel_launch(void* const* d_in, const int* in_sizes, int n_in, void* d_out, int out_size) {
  typedef CUresult (*EncFn)(CUtensorMap*, CUtensorMapDataType, cuuint32_t, void*, const cuuint64_t*, const cuuint64_t*, const cuuint32_t*, const cuuint32_t*,
                            CUtensorMapInterleave, CUtensorMapSwizzle, CUtensorMapL2promotion, CUtensorMapFloatOOBfill);
  static EncFn enc = nullptr; static void *scr = nullptr, *gt = nullptr;
  if (!enc) {
    void* fn = nullptr; cudaDriverEntryPointQueryResult qr;
    cudaGetDriverEntryPoint("cuTensorMapEncodeTiled", &fn, cudaEnableDefault, &qr);
    enc = (EncFn)fn;
    cudaGetSymbolAddress(&scr, g_s); cudaGetSymbolAddress(&gt, g_gtab);
    cudaFuncSetAttribute(fused_kernel, cudaFuncAttributeMaxDynamicSharedMemorySize, SM_TOTAL);
  }
  Params P; Maps M;
  const cuuint32_t es[2] = {1, 1};
  for (int i = 0; i < 5; i++) {
    const cuuint64_t gd[2] = {(cuuint64_t)(i < 2 ? D : (i == 2 ? 6 * D : F)), (cuuint64_t)(i < 2 ? L : D)}, gs[1] = {gd[0] * 2};
    const cuuint32_t bx[2] = {i == 0 ? 32u : (i == 1 ? 16u : 64u), i < 2 ? 256u : 160u};
    enc(&M.x[0] + i, CU_TENSOR_MAP_DATA_TYPE_BFLOAT16, 2, d_in[i < 2 ? 0 : (i == 2 ? 12 : 5 + i)], gd, gs, bx, es, CU_TENSOR_MAP_INTERLEAVE_NONE,
        i == 0 ? CU_TENSOR_MAP_SWIZZLE_64B : (i == 1 ? CU_TENSOR_MAP_SWIZZLE_32B : CU_TENSOR_MAP_SWIZZLE_128B), CU_TENSOR_MAP_L2_PROMOTION_NONE, CU_TENSOR_MAP_FLOAT_OOB_FILL_NONE);
  }
  {
    const cuuint32_t e5[5] = {1, 1, 1, 1, 1};
    const cuuint64_t g4[4] = {64, 128, 32, 5}, s4[3] = {5 * 4096, 128, 4096}; const cuuint32_t b4[4] = {64, 64, 2, 1};
    enc(&M.x1, CU_TENSOR_MAP_DATA_TYPE_BFLOAT16, 4, scr, g4, s4, b4, e5, CU_TENSOR_MAP_INTERLEAVE_NONE, CU_TENSOR_MAP_SWIZZLE_128B, CU_TENSOR_MAP_L2_PROMOTION_NONE, CU_TENSOR_MAP_FLOAT_OOB_FILL_NONE);
    const cuuint64_t g2[2] = {L, D}, s2[1] = {4096}; const cuuint32_t b2[2] = {64, 80};
    enc(&M.res, CU_TENSOR_MAP_DATA_TYPE_BFLOAT16, 2, scr, g2, s2, b2, e5, CU_TENSOR_MAP_INTERLEAVE_NONE, CU_TENSOR_MAP_SWIZZLE_128B, CU_TENSOR_MAP_L2_PROMOTION_NONE, CU_TENSOR_MAP_FLOAT_OOB_FILL_NONE);
    const cuuint64_t go[2] = {D, L}, so[1] = {D * 2}; const cuuint32_t bo[2] = {80, 16};
    enc(&M.out, CU_TENSOR_MAP_DATA_TYPE_BFLOAT16, 2, d_out, go, so, bo, e5, CU_TENSOR_MAP_INTERLEAVE_NONE, CU_TENSOR_MAP_SWIZZLE_NONE, CU_TENSOR_MAP_L2_PROMOTION_NONE, CU_TENSOR_MAP_FLOAT_OOB_FILL_NONE);
  }
  for (int i = 0; i < 2; i++) {
    const cuuint32_t e5[5] = {1, 1, 1, 1, 1}, b5[5] = {256, 2, i ? 5u : 6u, 2, 1};
    const cuuint64_t g5[5] = {256, 2, 216, 4, 5}, s5[4] = {4 * 216 * 2560, 2560, 216 * 2560, 512};
    enc(&M.w1[i], CU_TENSOR_MAP_DATA_TYPE_BFLOAT16, 5, (char*)scr + offsetof(Scratch, w1img), g5, s5, b5, e5, CU_TENSOR_MAP_INTERLEAVE_NONE, CU_TENSOR_MAP_SWIZZLE_NONE, CU_TENSOR_MAP_L2_PROMOTION_NONE, CU_TENSOR_MAP_FLOAT_OOB_FILL_NONE);
  }
  P.x = (const bf16*)d_in[0]; P.lar = (const bf16*)d_in[1]; P.aim = (const bf16*)d_in[2]; P.cre = (const bf16*)d_in[3]; P.cim = (const bf16*)d_in[4];
  P.ldt = (const bf16*)d_in[5]; P.dsk = (const bf16*)d_in[6]; P.wg = (const bf16*)d_in[8]; P.wu = (const bf16*)d_in[9]; P.wd = (const bf16*)d_in[10];
  P.c = (const bf16*)d_in[11]; P.wm = (const bf16*)d_in[12]; P.out = (bf16*)d_out; P.zero = 0; P.s = (Scratch*)scr; P.gtab = gt;
  fused_kernel<<<132, 768, SM_TOTAL>>>(P, M);
}
```
